```python
import torch

def _softmax(x, axis=-1):
    return torch.softmax(x, dim=axis)
def _gelu(x):
    return torch.nn.functional.gelu(x, approximate="tanh")
def _silu(x):
    return torch.nn.functional.silu(x)
def _sigmoid(x):
    return torch.sigmoid(x)
def _layernorm(x, axis=-1, eps=1e-5):
    m = x.mean(dim=axis, keepdim=True)
    v = x.var(dim=axis, keepdim=True, unbiased=False)
    return (x - m) / torch.sqrt(v + eps)
def _scatter_add(tgt, idx, src, axis=0):
    return tgt.clone().index_add_(axis, idx, src)
def _segment_sum(src, seg, n):
    out = torch.zeros((n,) + src.shape[1:], dtype=src.dtype)
    return out.index_add_(0, seg, src)
def _pad(x, pw):
    flat = tuple(v for pair in reversed(pw) for v in pair)
    return torch.nn.functional.pad(x, flat)

kernel_name = 'sequential_preLN__spectral_gfnet__glu_gated_geglu__prompt'

def setup_inputs():

    _w = (lambda a: (lambda t: t.to(torch.bfloat16) if t.is_floating_point() else t)(torch.as_tensor(a)))
    def _A_setup():
        B, S, D = 1, 2048, 512
        Df = D // 2 + 1
        return {
            "x": _w((lambda *s: torch.randn(*s, dtype=torch.bfloat16) * 0.05)(B, S, D)),
            "w_r": _w((lambda *s: torch.randn(*s, dtype=torch.bfloat16) * 0.4)(S, Df) * 0.02),
            "w_i": _w((lambda *s: torch.randn(*s, dtype=torch.bfloat16) * 0.4)(S, Df) * 0.02),
        }
    _A_in = _A_setup()

    def _B_setup():
        B, S, Dm, Df = 1, 2048, 512, 1376
        return {
            "x": _w((lambda *s: torch.randn(*s, dtype=torch.bfloat16) * 0.05)(B, S, Dm)),
            "w_gate": _w((lambda *s: torch.randn(*s, dtype=torch.bfloat16) * 0.4)(Dm, Df) * (Dm ** -0.5)),
            "w_up": _w((lambda *s: torch.randn(*s, dtype=torch.bfloat16) * 0.4)(Dm, Df) * (Dm ** -0.5)),
            "w_down": _w((lambda *s: torch.randn(*s, dtype=torch.bfloat16) * 0.4)(Df, Dm) * (Df ** -0.5)),
        }
    _B_in = _B_setup()

    return {
        "A_x": _A_in["x"],
        "A_w_r": _A_in["w_r"],
        "A_w_i": _A_in["w_i"],
        "B_x": _B_in["x"],
        "B_w_gate": _B_in["w_gate"],
        "B_w_up": _B_in["w_up"],
        "B_w_down": _B_in["w_down"],
    }

def reference(A_x, A_w_r, A_w_i, B_x, B_w_gate, B_w_up, B_w_down):
    def _A_ref(x, w_r, w_i):
        B, S, D = x.shape
        X = (lambda x, axes=(-2,-1): torch.fft.rfft2(x.float(), dim=axes))(x, axes=(-2, -1))
        W = w_r + 1j * w_i
        X = X * W
        y = (lambda x, s, axes=(-2,-1): torch.fft.irfft2(x, s=s, dim=axes).to(torch.bfloat16))(X, (S, D), axes=(-2, -1))
        return y

    def _B_ref(x, w_gate, w_up, w_down):
        g = torch.einsum("bsd,df->bsf", x, w_gate)
        u = torch.einsum("bsd,df->bsf", x, w_up)
        h = _gelu(g) * u
        return torch.einsum("bsf,fd->bsd", h, w_down)

    x = A_x
    h = x + _A_ref(_layernorm(x, axis=-1), A_w_r, A_w_i)
    h2 = h + _B_ref(_layernorm(h, axis=-1), B_w_gate, B_w_up, B_w_down)
    return h2
```

```cpp
#include <cuda_runtime.h>
#include <cuda_bf16.h>
#include <cuda_fp16.h>
#include <cuda.h>
#include <stdint.h>

#define WATCHDOG 0
#define GATE_W 1
#define GATE_X 1
#define XPROBE 0
#define PROFMASK ((1ull << 17) | (1ull << 12) | (1ull << 3) | (1ull << 7) | (1ull << 11) | (1ull << 13) | (1ull << 14) | (1ull << 16) | (1ull << 4) | (1ull << 8))
#define FILT_PF 1
#define PP0 11
#define DELAY1 0
#define DELAY2 0
#define NOFENCE_W 0
#define HINT1 -1
#define HINT2 -1
#define PROFILE 0

namespace {

constexpr int D_ = 512, DF_ = 257, F_ = 1376;
constexpr int NCTA = 128;
constexpr int REG_CONS = 216, REG_SIDE = 72;
constexpr int NTHREADS = 384;

constexpr int SLOT = 30720, NSLOT = 6;
constexpr int OFF_RECV = NSLOT * SLOT;
constexpr int OFF_X = OFF_RECV;
constexpr int XPLANE = 1312, XBLK = 160;
constexpr int OFF_FILT = OFF_RECV + 21504;
constexpr int OFF_TAB = 5 * SLOT;
constexpr int OFF_BAR = OFF_RECV + 45056;
constexpr int BAR_FULL = OFF_BAR, BAR_EMPTY = OFF_BAR + 48, BAR_TABA = OFF_BAR + 96, BAR_TABB = OFF_BAR + 104,
              BAR_RECV = OFF_BAR + 112, BAR_PACK = OFF_BAR + 176, BAR_PEER = OFF_BAR + 184, BAR_FILT = OFF_BAR + 192;
constexpr int OFF_MISC = OFF_BAR + 208;
constexpr int SMEM_BYTES = OFF_BAR + 256;
constexpr int TAB_A_BYTES = 14 * 512, TAB_BYTES = 41 * 512;

__device__ const uint4 g_tab[1312] = {
{0x34003400,0x34003400,0x34003400,0x34003400},{0x34003400,0xb400b400,0x34003400,0xb400b400},
{0x34003400,0x34003400,0x34003400,0x34003400},{0x34003400,0xb400b400,0x34003400,0xb400b400},
{0x3400,0x3400,0xb400,0xb400},{0xae1f3364,0x2e1fb364,0x2e1fb364,0xae1f3364},
{0xb1a831a8,0xb1a831a8,0x31a8b1a8,0x31a8b1a8},{0xb3642e1f,0x3364ae1f,0x3364ae1f,0xb3642e1f},
{0xb4003400,0xb4003400,0xb4003400,0xb4003400},{0xb1a831a8,0x31a8b1a8,0xb1a831a8,0x31a8b1a8},
{0x0,0x0,0x0,0x0},{0x31a8b1a8,0xb1a831a8,0x31a8b1a8,0xb1a831a8},
{0x3400,0x3400,0xb400,0xb400},{0x33642e1f,0xb364ae1f,0xb364ae1f,0x33642e1f},
{0x31a8b1a8,0x31a8b1a8,0xb1a831a8,0xb1a831a8},{0xae1fb364,0x2e1f3364,0x2e1f3364,0xae1fb364},
{0x34003400,0x34003400,0x34003400,0x34003400},{0x0,0x0,0x0,0x0},
{0xb400b400,0xb400b400,0xb400b400,0xb400b400},{0x0,0x0,0x0,0x0},
{0x3400,0x3400,0xb400,0xb400},{0xb364ae1f,0x33642e1f,0x33642e1f,0xb364ae1f},
{0x31a8b1a8,0x31a8b1a8,0xb1a831a8,0xb1a831a8},{0x2e1f3364,0xae1fb364,0xae1fb364,0x2e1f3364},
{0xb4003400,0xb4003400,0xb4003400,0xb4003400},{0x31a8b1a8,0xb1a831a8,0x31a8b1a8,0xb1a831a8},
{0x0,0x0,0x0,0x0},{0xb1a831a8,0x31a8b1a8,0xb1a831a8,0x31a8b1a8},
{0x3400,0x3400,0xb400,0xb400},{0x2e1fb364,0xae1f3364,0xae1f3364,0x2e1fb364},
{0xb1a831a8,0xb1a831a8,0x31a8b1a8,0x31a8b1a8},{0x3364ae1f,0xb3642e1f,0xb3642e1f,0x3364ae1f},
{0x0,0x0,0x0,0x0},{0x0,0x0,0x0,0x0},
{0x0,0x0,0x0,0x0},{0x0,0x0,0x0,0x0},
{0x34000000,0x34000000,0xb4000000,0xb4000000},{0x33642e1f,0xb364ae1f,0xb364ae1f,0x33642e1f},
{0x31a831a8,0x31a831a8,0xb1a8b1a8,0xb1a8b1a8},{0x2e1f3364,0xae1fb364,0xae1fb364,0x2e1f3364},
{0x0,0x0,0x0,0x0},{0xb1a831a8,0x31a8b1a8,0xb1a831a8,0x31a8b1a8},
{0xb4003400,0xb4003400,0xb4003400,0xb4003400},{0xb1a831a8,0x31a8b1a8,0xb1a831a8,0x31a8b1a8},
{0xb4000000,0xb4000000,0x34000000,0x34000000},{0xae1f3364,0x2e1fb364,0x2e1fb364,0xae1f3364},
{0x31a831a8,0x31a831a8,0xb1a8b1a8,0xb1a8b1a8},{0x3364ae1f,0xb3642e1f,0xb3642e1f,0x3364ae1f},
{0x0,0x0,0x0,0x0},{0x34003400,0xb400b400,0x34003400,0xb400b400},
{0x0,0x0,0x0,0x0},{0xb400b400,0x34003400,0xb400b400,0x34003400},
{0x34000000,0x34000000,0xb4000000,0xb4000000},{0xae1f3364,0x2e1fb364,0x2e1fb364,0xae1f3364},
{0xb1a8b1a8,0xb1a8b1a8,0x31a831a8,0x31a831a8},{0x3364ae1f,0xb3642e1f,0xb3642e1f,0x3364ae1f},
{0x0,0x0,0x0,0x0},{0xb1a831a8,0x31a8b1a8,0xb1a831a8,0x31a8b1a8},
{0x3400b400,0x3400b400,0x3400b400,0x3400b400},{0xb1a831a8,0x31a8b1a8,0xb1a831a8,0x31a8b1a8},
{0xb4000000,0xb4000000,0x34000000,0x34000000},{0x33642e1f,0xb364ae1f,0xb364ae1f,0x33642e1f},
{0xb1a8b1a8,0xb1a8b1a8,0x31a831a8,0x31a831a8},{0x2e1f3364,0xae1fb364,0xae1fb364,0x2e1f3364},
{0x31a831a8,0x0,0x313a31a8,0x2c540000},{0x31a831a8,0x0,0x2c543000,0x313a3000},
{0x31a831a8,0x0,0xac540000,0x313a31a8},{0x31a831a8,0x0,0xb13ab000,0x2c543000},
{0x31a631a8,0x20710000,0x311d31a8,0x2cd60000},{0x319831a1,0x26a42470,0x297f2f2d,0x317d305f},
{0x317d318c,0x297f286a,0xaebda86a,0x308b318c},{0x3154316a,0x2b9f2a92,0xb1a6b0fd,0x20712d55},
{0x31a131a8,0x24700000,0x30fd31a8,0x2d550000},{0x316a318c,0x2a92286a,0x24702e49,0x31a130b4},
{0x30fd313a,0x2d552c54,0xb05fac54,0x2f2d313a},{0x305f30b4,0x2f2d2e49,0xb16ab18c,0xaa92286a},
{0x319831a8,0x26a40000,0x30da31a8,0x2dd10000},{0x311d316a,0x2cd62a92,0xa0712d55,0x31a630fd},
{0x303130b4,0x2f992e49,0xb11dae49,0x2cd630b4},{0x2dd12f2d,0x30da305f,0xb08bb1a1,0xaebda470},
{0x318c31a8,0x286a0000,0x30b431a8,0x2e490000},{0x30b4313a,0x2e492c54,0xa86a2c54,0x318c313a},
{0x2e493000,0x30b43000,0xb18cb000,0x286a3000},{0x286a2c54,0x318c313a,0xae49b13a,0xb0b4ac54},
{0x317d31a8,0x297f0000,0x308b31a8,0x2ebd0000},{0x303130fd,0x2f992d55,0xab9f2a92,0x3154316a},
{0x2b9f2e49,0x315430b4,0xb1a6b0b4,0xa0712e49},{0xa6a42470,0x319831a1,0xa97fb05f,0xb17daf2d},
{0x316a31a8,0x2a920000,0x305f31a8,0x2f2d0000},{0x2f2d30b4,0x305f2e49,0xad55286a,0x30fd318c},
{0x24702c54,0x31a1313a,0xb16ab13a,0xaa922c54},{0xad55a86a,0x30fd318c,0x2470ae49,0xb1a1b0b4},
{0x315431a8,0x2b9f0000,0x303131a8,0x2f990000},{0x2dd1305f,0x30da2f2d,0xaebd2470,0x308b31a1},
{0xa6a4286a,0x3198318c,0xb0dab18c,0xadd1286a},{0xb031ad55,0x2f9930fd,0x2cd6aa92,0xb11db16a},
{0x31a831a8,0x0,0x30fd31a1,0x2d552470},{0x31a831a8,0x0,0x2a922f2d,0x316a305f},
{0x31a831a8,0x0,0xad55a470,0x30fd31a1},{0x31a831a8,0x0,0xb16ab05f,0x2a922f2d},
{0x31a531a8,0x218d1871,0x30d1319f,0x2def24fd},{0x3196319f,0x273024fd,0x26172e2b,0x319b30be},
{0x31783189,0x29c428b0,0xafb3aad5,0x30253165},{0x314d3165,0x2be22ad5,0xb1a5b141,0xa18d2c33},
{0x319d31a8,0x258a1c71,0x30a0319d,0x2e84258a},{0x315f3185,0x2b1928f5,0x9c712d16,0x31a8310e},
{0x30ec312c,0x2d942c96,0xb0c7ad94,0x2e0e30ec},{0x304930a0,0x2f642e84,0xb12cb1a4,0xac9622a9},
{0x319031a7,0x28241eaa,0x306b319b,0x2f122617},{0x31053159,0x2d362b5c,0xa8242be2,0x3190314d},
{0x300c3096,0x2fe72ea1,0xb165af7f,0x2ad5303d},{0x2d752eda,0x30f53080,0xb00cb181,0xafe7a93a},
{0x317d31a6,0x297f2071,0x30313198,0x2f9926a4},{0x308b311d,0x2ebd2cd6,0xab9f297f,0x3154317d},
{0x2dd12f99,0x30da3031,0xb1a6b08b,0x20712ebd},{0x26a42b9f,0x31983154,0xacd6b0da,0xb11dadd1},
{0x316531a5,0x2ad5218d,0x2fe73196,0x300c2730},{0x2fe730d1,0x300c2def,0xad752617,0x30f5319b},
{0x2a4d2db2,0x316f30e3,0xb189b125,0xa8b02cb6},{0xa8b01eaa,0x318931a7,0xa3c4af7f,0xb1a3b03d},
{0x314731a4,0x2c1222a9,0x2f643193,0x304927bd},{0x2e843076,0x30a02ef6,0xaef61c71,0x307631a8},
{0x1c712b19,0x31a8315f,0xb10eb185,0xad1628f5},{0xae0eaa09,0x30c73174,0x2a09ac96,0xb174b12c},
{0x312531a3,0x2cb623c4,0x2eda3190,0x30802824},{0x2cf6300c,0x31152fe7,0xb025a3c4,0x2fb331a3},
{0xa93a24fd,0x3181319f,0xb03db1a8,0xaf7f1871},{0xb080ae2b,0x2eda30be,0x2ea1a4fd,0xb096b19f},
{0x31a831a8,0x0,0x30b4318c,0x2e49286a},{0x31a831a8,0x0,0x286a2e49,0x318c30b4},
{0x31a831a8,0x0,0xae49a86a,0x30b4318c},{0x31a831a8,0x0,0xb18cb0b4,0x286a2e49},
{0x31a431a8,0x22a91c71,0x30763185,0x2ef628f5},{0x3193319d,0x27bd258a,0x1c712d16,0x31a8310e},
{0x31743185,0x2a0928f5,0xb049ac96,0x2f64312c},{0x3147315f,0x2c122b19,0xb193b174,0xa7bd2a09},
{0x319831a6,0x26a42071,0x3031317d,0x2f99297f},{0x3154317d,0x2b9f297f,0xa6a42b9f,0x31983154},
{0x30da311d,0x2dd12cd6,0xb11daebd,0x2cd6308b},{0x3031308b,0x2f992ebd,0xb0dab1a6,0xadd1a071},
{0x318531a4,0x28f522a9,0x2fcd3174,0x30192a09},{0x30ec3147,0x2d942c12,0xab1928f5,0x315f3185},
{0x2fcd3076,0x30192ef6,0xb193b049,0x27bd2f64},{0x2d162e84,0x310e30a0,0xaef6b147,0xb076ac12},
{0x316a31a1,0x2a922470,0x2f2d316a,0x305f2a92},{0x305f30fd,0x2f2d2d55,0xad552470,0x30fd31a1},
{0x2d552f2d,0x30fd305f,0xb1a1b0fd,0xa4702d55},{0x24702a92,0x31a1316a,0xaa92b05f,0xb16aaf2d},
{0x3147319d,0x2c12258a,0x2e84315f,0x30a02b19},{0x2f6430a0,0x30492e84,0xaef69c71,0x307631a8},
{0x28f52d16,0x3185310e,0xb147b174,0xac122a09},{0xaa099c71,0x317431a8,0x22a9ae0e,0xb1a4b0c7},
{0x311d3198,0x2cd626a4,0x2dd13154,0x30da2b9f},{0x2dd13031,0x30da2f99,0xb031a6a4,0x2f993198},
{0xa071297f,0x31a6317d,0xb08bb1a6,0xaebd2071},{0xaebdab9f,0x308b3154,0x2cd6a97f,0xb11db17d},
{0x30ec3193,0x2d9427bd,0x2d163147,0x310e2c12},{0x2c122f64,0x31473049,0xb0c7aa09,0x2e0e3174},
{0xab191c71,0x315f31a8,0xaef6b193,0xb076a7bd},{0xb0c7aef6,0x2e0e3076,0x301922a9,0xafcdb1a4},
{0x31a831a8,0x0,0x305f316a,0x2f2d2a92},{0x31a831a8,0x0,0x24702d55,0x31a130fd},
{0x31a831a8,0x0,0xaf2daa92,0x305f316a},{0x31a831a8,0x0,0xb1a1b0fd,0x24702d55},
{0x31a331a7,0x23c41eaa,0x300c3159,0x2fe72b5c},{0x3190319b,0x28242617,0xa3c42be2,0x31a3314d},
{0x316f3181,0x2a4d293a,0xb0aaadb2,0x2e6730e3},{0x31413159,0x2c332b5c,0xb16fb196,0xaa4d2730},
{0x319331a4,0x27bd22a9,0x2f643147,0x30492c12},{0x31473174,0x2c122a09,0xaa0928f5,0x31743185},
{0x30c7310e,0x2e0e2d16,0xb15fafcd,0x2b193019},{0x30193076,0x2fcd2ef6,0xb076b193,0xaef6a7bd},
{0x3178319f,0x29c424fd,0x2ea13133,0x30962c75},{0x30d13133,0x2def2c75,0xacf623c4,0x311531a3},
{0x2f7f3054,0x303d2f49,0xb1a7b0be,0x1eaa2e2b},{0x2cb62e2b,0x312530be,0xadb2b0f5,0xb0e3ad75},
{0x31543198,0x2b9f26a4,0x2dd1311d,0x30da2cd6},{0x303130da,0x2f992dd1,0xaebda071,0x308b31a6},
{0x2cd62ebd,0x311d308b,0xb17db154,0xa97f2b9f},{0x2071297f,0x31a6317d,0xa6a4af99,0xb198b031},
{0x31253190,0x2cb62824,0x2cf63105,0x31152d36},{0x2eda306b,0x30802f12,0xb025a824,0x2fb33190},
{0x27302c75,0x31963133,0xb0e3b19f,0xadb224fd},{0xab5ca3c4,0x315931a3,0x293aac75,0xb181b133},
{0x30ec3185,0x2d9428f5,0x2c1230ec,0x31472d94},{0x2d162fcd,0x310e3019,0xb0c7ab19,0x2e0e315f},
{0xa58a27bd,0x319d3193,0xafcdb19d,0xb019a58a},{0xaf64ac96,0x3049312c,0x2e84a2a9,0xb0a0b1a4},
{0x30aa3178,0x2e6729c4,0x2a4d30d1,0x316f2def},{0x2a4d2ea1,0x316f3096,0xb141acf6,0x2c333115},
{0xac75a18d,0x313331a5,0xad36b14d,0xb105abe2},{0xb105afb3,0x2d363025,0x30be29c4,0xae2bb178},
{0x3c003c00,0x3c003c00,0x3c003c00,0x0},{0x3c003c00,0x3c003c00,0x3c003c00,0x0},
{0x3c003c00,0x3c003c00,0x3c003c00,0x0},{0x3c003c00,0x3c003c00,0x3c003c00,0x0},
{0x39a83c00,0x38723bd9,0x39a83c00,0xbaa7b23e},{0xb9a80000,0xbaa7b23e,0xb9a80000,0xb872bbd9},
{0xb9a8bc00,0xb872bbd9,0xb9a8bc00,0x3aa7323e},{0x39a80000,0x3aa7323e,0x39a80000,0x38723bd9},
{0x3c00,0xb61f3b64,0x3c00,0xbb64b61f},{0xbc00,0x361fbb64,0xbc00,0x3b64361f},
{0x3c00,0xb61f3b64,0x3c00,0xbb64b61f},{0xbc00,0x361fbb64,0xbc00,0x3b64361f},
{0xb9a83c00,0xbbd93aa7,0xb9a83c00,0xb23eb872},{0x39a80000,0x323e3872,0x39a80000,0xbbd93aa7},
{0x39a8bc00,0x3bd9baa7,0x39a8bc00,0x323e3872},{0xb9a80000,0xb23eb872,0xb9a80000,0x3bd9baa7},
{0xbc003c00,0xb9a839a8,0xbc003c00,0x39a8b9a8},{0xbc003c00,0xb9a839a8,0xbc003c00,0x39a8b9a8},
{0xbc003c00,0xb9a839a8,0xbc003c00,0x39a8b9a8},{0xbc003c00,0xb9a839a8,0xbc003c00,0x39a8b9a8},
{0xb9a83c00,0x323e3872,0xb9a83c00,0x3bd9baa7},{0x39a80000,0x3bd9baa7,0x39a80000,0xb23eb872},
{0x39a8bc00,0xb23eb872,0x39a8bc00,0xbbd93aa7},{0xb9a80000,0xbbd93aa7,0xb9a80000,0x323e3872},
{0x3c00,0x3b64361f,0x3c00,0x361fbb64},{0xbc00,0xbb64b61f,0xbc00,0xb61f3b64},
{0x3c00,0x3b64361f,0x3c00,0x361fbb64},{0xbc00,0xbb64b61f,0xbc00,0xb61f3b64},
{0x39a83c00,0x3aa7323e,0x39a83c00,0xb872bbd9},{0xb9a80000,0x38723bd9,0xb9a80000,0x3aa7323e},
{0xb9a8bc00,0xbaa7b23e,0xb9a8bc00,0x38723bd9},{0x39a80000,0xb872bbd9,0x39a80000,0xbaa7b23e},
{0x3c003c00,0xbc00bc00,0x3c003c00,0x0},{0x3c003c00,0xbc00bc00,0x3c003c00,0x0},
{0x3c003c00,0xbc00bc00,0x3c003c00,0x0},{0x3c003c00,0xbc00bc00,0x3c003c00,0x0},
{0x39a83c00,0xb872bbd9,0x39a83c00,0x3aa7323e},{0xb9a80000,0x3aa7323e,0xb9a80000,0x38723bd9},
{0xb9a8bc00,0x38723bd9,0xb9a8bc00,0xbaa7b23e},{0x39a80000,0xbaa7b23e,0x39a80000,0xb872bbd9},
{0x3c00,0x361fbb64,0x3c00,0x3b64361f},{0xbc00,0xb61f3b64,0xbc00,0xbb64b61f},
{0x3c00,0x361fbb64,0x3c00,0x3b64361f},{0xbc00,0xb61f3b64,0xbc00,0xbb64b61f},
{0xb9a83c00,0x3bd9baa7,0xb9a83c00,0x323e3872},{0x39a80000,0xb23eb872,0x39a80000,0x3bd9baa7},
{0x39a8bc00,0xbbd93aa7,0x39a8bc00,0xb23eb872},{0xb9a80000,0x323e3872,0xb9a80000,0xbbd93aa7},
{0xbc003c00,0x39a8b9a8,0xbc003c00,0xb9a839a8},{0xbc003c00,0x39a8b9a8,0xbc003c00,0xb9a839a8},
{0xbc003c00,0x39a8b9a8,0xbc003c00,0xb9a839a8},{0xbc003c00,0x39a8b9a8,0xbc003c00,0xb9a839a8},
{0xb9a83c00,0xb23eb872,0xb9a83c00,0xbbd93aa7},{0x39a80000,0xbbd93aa7,0x39a80000,0x323e3872},
{0x39a8bc00,0x323e3872,0x39a8bc00,0x3bd9baa7},{0xb9a80000,0x3bd9baa7,0xb9a80000,0xb23eb872},
{0x3c00,0xbb64b61f,0x3c00,0xb61f3b64},{0xbc00,0x3b64361f,0xbc00,0x361fbb64},
{0x3c00,0xbb64b61f,0x3c00,0xb61f3b64},{0xbc00,0x3b64361f,0xbc00,0x361fbb64},
{0x39a83c00,0xbaa7b23e,0x39a83c00,0x38723bd9},{0xb9a80000,0xb872bbd9,0xb9a80000,0xbaa7b23e},
{0xb9a8bc00,0x3aa7323e,0xb9a8bc00,0xb872bbd9},{0x39a80000,0x38723bd9,0x39a80000,0x3aa7323e},
{0x3c003c00,0x3c003c00,0xbc00bc00,0x0},{0x3c003c00,0x3c003c00,0xbc00bc00,0x0},
{0x3c003c00,0x3c003c00,0xbc00bc00,0x0},{0x3c003c00,0x3c003c00,0xbc00bc00,0x0},
{0x361f3b64,0x323e3aa7,0xb61fbb64,0x3bd93872},{0xbb64b61f,0xbbd9b872,0x3b64361f,0x323e3aa7},
{0xb61fbb64,0xb23ebaa7,0x361f3b64,0xbbd9b872},{0x3b64361f,0x3bd93872,0xbb64b61f,0xb23ebaa7},
{0xb9a839a8,0xbb64361f,0x39a8b9a8,0x361f3b64},{0x39a8b9a8,0x3b64b61f,0xb9a839a8,0xb61fbb64},
{0xb9a839a8,0xbb64361f,0x39a8b9a8,0x361f3b64},{0x39a8b9a8,0x3b64b61f,0xb9a839a8,0xb61fbb64},
{0xbb64361f,0xb872b23e,0x3b64b61f,0xbaa73bd9},{0xb61f3b64,0xbaa73bd9,0x361fbb64,0x3872323e},
{0x3b64b61f,0x3872323e,0xbb64361f,0x3aa7bbd9},{0x361fbb64,0x3aa7bbd9,0xb61f3b64,0xb872b23e},
{0x0,0x39a8b9a8,0x0,0xb9a839a8},{0x0,0x39a8b9a8,0x0,0xb9a839a8},
{0x0,0x39a8b9a8,0x0,0xb9a839a8},{0x0,0x39a8b9a8,0x0,0xb9a839a8},
{0x3b64b61f,0x3aa7bbd9,0xbb64361f,0x3872323e},{0x361fbb64,0xb872b23e,0xb61f3b64,0x3aa7bbd9},
{0xbb64361f,0xbaa73bd9,0x3b64b61f,0xb872b23e},{0xb61f3b64,0x3872323e,0x361fbb64,0xbaa73bd9},
{0x39a8b9a8,0xb61fbb64,0xb9a839a8,0x3b64b61f},{0xb9a839a8,0x361f3b64,0x39a8b9a8,0xbb64361f},
{0x39a8b9a8,0xb61fbb64,0xb9a839a8,0x3b64b61f},{0xb9a839a8,0x361f3b64,0x39a8b9a8,0xbb64361f},
{0xb61fbb64,0xbbd9b872,0x361f3b64,0xb23ebaa7},{0x3b64361f,0xb23ebaa7,0xbb64b61f,0x3bd93872},
{0x361f3b64,0x3bd93872,0xb61fbb64,0x323e3aa7},{0xbb64b61f,0x323e3aa7,0x3b64361f,0xbbd9b872},
{0x3c003c00,0xbc00bc00,0xbc00bc00,0x0},{0x3c003c00,0xbc00bc00,0xbc00bc00,0x0},
{0x3c003c00,0xbc00bc00,0xbc00bc00,0x0},{0x3c003c00,0xbc00bc00,0xbc00bc00,0x0},
{0x361f3b64,0xb23ebaa7,0xb61fbb64,0xbbd9b872},{0xbb64b61f,0x3bd93872,0x3b64361f,0xb23ebaa7},
{0xb61fbb64,0x323e3aa7,0x361f3b64,0x3bd93872},{0x3b64361f,0xbbd9b872,0xbb64b61f,0x323e3aa7},
{0xb9a839a8,0x3b64b61f,0x39a8b9a8,0xb61fbb64},{0x39a8b9a8,0xbb64361f,0xb9a839a8,0x361f3b64},
{0xb9a839a8,0x3b64b61f,0x39a8b9a8,0xb61fbb64},{0x39a8b9a8,0xbb64361f,0xb9a839a8,0x361f3b64},
{0xbb64361f,0x3872323e,0x3b64b61f,0x3aa7bbd9},{0xb61f3b64,0x3aa7bbd9,0x361fbb64,0xb872b23e},
{0x3b64b61f,0xb872b23e,0xbb64361f,0xbaa73bd9},{0x361fbb64,0xbaa73bd9,0xb61f3b64,0x3872323e},
{0x0,0xb9a839a8,0x0,0x39a8b9a8},{0x0,0xb9a839a8,0x0,0x39a8b9a8},
{0x0,0xb9a839a8,0x0,0x39a8b9a8},{0x0,0xb9a839a8,0x0,0x39a8b9a8},
{0x3b64b61f,0xbaa73bd9,0xbb64361f,0xb872b23e},{0x361fbb64,0x3872323e,0xb61f3b64,0xbaa73bd9},
{0xbb64361f,0x3aa7bbd9,0x3b64b61f,0x3872323e},{0xb61f3b64,0xb872b23e,0x361fbb64,0x3aa7bbd9},
{0x39a8b9a8,0x361f3b64,0xb9a839a8,0xbb64361f},{0xb9a839a8,0xb61fbb64,0x39a8b9a8,0x3b64b61f},
{0x39a8b9a8,0x361f3b64,0xb9a839a8,0xbb64361f},{0xb9a839a8,0xb61fbb64,0x39a8b9a8,0x3b64b61f},
{0xb61fbb64,0x3bd93872,0x361f3b64,0x323e3aa7},{0x3b64361f,0x323e3aa7,0xbb64b61f,0xbbd9b872},
{0x361f3b64,0xbbd9b872,0xb61fbb64,0xb23ebaa7},{0xbb64b61f,0xb23ebaa7,0x3b64361f,0x3bd93872},
{0x0,0x0,0x0,0x3c003c00},{0x0,0x0,0x0,0x3c003c00},
{0x0,0x0,0x0,0x3c003c00},{0x0,0x0,0x0,0x3c003c00},
{0x39a80000,0x3aa7323e,0x39a80000,0x38723bd9},{0x39a83c00,0x38723bd9,0x39a83c00,0xbaa7b23e},
{0xb9a80000,0xbaa7b23e,0xb9a80000,0xb872bbd9},{0xb9a8bc00,0xb872bbd9,0xb9a8bc00,0x3aa7323e},
{0x3c000000,0x3b64361f,0x3c000000,0xb61f3b64},{0xbc000000,0xbb64b61f,0xbc000000,0x361fbb64},
{0x3c000000,0x3b64361f,0x3c000000,0xb61f3b64},{0xbc000000,0xbb64b61f,0xbc000000,0x361fbb64},
{0x39a80000,0x323e3872,0x39a80000,0xbbd93aa7},{0x39a8bc00,0x3bd9baa7,0x39a8bc00,0x323e3872},
{0xb9a80000,0xb23eb872,0xb9a80000,0x3bd9baa7},{0xb9a83c00,0xbbd93aa7,0xb9a83c00,0xb23eb872},
{0x0,0xb9a839a8,0x0,0xb9a839a8},{0x0,0xb9a839a8,0x0,0xb9a839a8},
{0x0,0xb9a839a8,0x0,0xb9a839a8},{0x0,0xb9a839a8,0x0,0xb9a839a8},
{0xb9a80000,0xbbd93aa7,0xb9a80000,0x323e3872},{0xb9a83c00,0x323e3872,0xb9a83c00,0x3bd9baa7},
{0x39a80000,0x3bd9baa7,0x39a80000,0xb23eb872},{0x39a8bc00,0xb23eb872,0x39a8bc00,0xbbd93aa7},
{0xbc000000,0xb61f3b64,0xbc000000,0x3b64361f},{0x3c000000,0x361fbb64,0x3c000000,0xbb64b61f},
{0xbc000000,0xb61f3b64,0xbc000000,0x3b64361f},{0x3c000000,0x361fbb64,0x3c000000,0xbb64b61f},
{0xb9a80000,0x38723bd9,0xb9a80000,0x3aa7323e},{0xb9a8bc00,0xbaa7b23e,0xb9a8bc00,0x38723bd9},
{0x39a80000,0xb872bbd9,0x39a80000,0xbaa7b23e},{0x39a83c00,0x3aa7323e,0x39a83c00,0xb872bbd9},
{0x0,0x0,0x0,0xbc00bc00},{0x0,0x0,0x0,0xbc00bc00},
{0x0,0x0,0x0,0xbc00bc00},{0x0,0x0,0x0,0xbc00bc00},
{0x39a80000,0xbaa7b23e,0x39a80000,0xb872bbd9},{0x39a83c00,0xb872bbd9,0x39a83c00,0x3aa7323e},
{0xb9a80000,0x3aa7323e,0xb9a80000,0x38723bd9},{0xb9a8bc00,0x38723bd9,0xb9a8bc00,0xbaa7b23e},
{0x3c000000,0xbb64b61f,0x3c000000,0x361fbb64},{0xbc000000,0x3b64361f,0xbc000000,0xb61f3b64},
{0x3c000000,0xbb64b61f,0x3c000000,0x361fbb64},{0xbc000000,0x3b64361f,0xbc000000,0xb61f3b64},
{0x39a80000,0xb23eb872,0x39a80000,0x3bd9baa7},{0x39a8bc00,0xbbd93aa7,0x39a8bc00,0xb23eb872},
{0xb9a80000,0x323e3872,0xb9a80000,0xbbd93aa7},{0xb9a83c00,0x3bd9baa7,0xb9a83c00,0x323e3872},
{0x0,0x39a8b9a8,0x0,0x39a8b9a8},{0x0,0x39a8b9a8,0x0,0x39a8b9a8},
{0x0,0x39a8b9a8,0x0,0x39a8b9a8},{0x0,0x39a8b9a8,0x0,0x39a8b9a8},
{0xb9a80000,0x3bd9baa7,0xb9a80000,0xb23eb872},{0xb9a83c00,0xb23eb872,0xb9a83c00,0xbbd93aa7},
{0x39a80000,0xbbd93aa7,0x39a80000,0x323e3872},{0x39a8bc00,0x323e3872,0x39a8bc00,0x3bd9baa7},
{0xbc000000,0x361fbb64,0xbc000000,0xbb64b61f},{0x3c000000,0xb61f3b64,0x3c000000,0x3b64361f},
{0xbc000000,0x361fbb64,0xbc000000,0xbb64b61f},{0x3c000000,0xb61f3b64,0x3c000000,0x3b64361f},
{0xb9a80000,0xb872bbd9,0xb9a80000,0xbaa7b23e},{0xb9a8bc00,0x3aa7323e,0xb9a8bc00,0xb872bbd9},
{0x39a80000,0x38723bd9,0x39a80000,0x3aa7323e},{0x39a83c00,0xbaa7b23e,0x39a83c00,0x38723bd9},
{0x0,0x0,0x0,0xbc00bc00},{0x0,0x0,0x0,0xbc00bc00},
{0x0,0x0,0x0,0xbc00bc00},{0x0,0x0,0x0,0xbc00bc00},
{0x3b64361f,0x3bd93872,0xbb64b61f,0xb23ebaa7},{0x361f3b64,0x323e3aa7,0xb61fbb64,0x3bd93872},
{0xbb64b61f,0xbbd9b872,0x3b64361f,0x323e3aa7},{0xb61fbb64,0xb23ebaa7,0x361f3b64,0xbbd9b872},
{0x39a839a8,0x361f3b64,0xb9a8b9a8,0x3b64b61f},{0xb9a8b9a8,0xb61fbb64,0x39a839a8,0xbb64361f},
{0x39a839a8,0x361f3b64,0xb9a8b9a8,0x3b64b61f},{0xb9a8b9a8,0xb61fbb64,0x39a839a8,0xbb64361f},
{0xb61f3b64,0xbaa73bd9,0x361fbb64,0x3872323e},{0x3b64b61f,0x3872323e,0xbb64361f,0x3aa7bbd9},
{0x361fbb64,0x3aa7bbd9,0xb61f3b64,0xb872b23e},{0xbb64361f,0xb872b23e,0x3b64b61f,0xbaa73bd9},
{0xbc003c00,0xb9a839a8,0x3c00bc00,0xb9a839a8},{0xbc003c00,0xb9a839a8,0x3c00bc00,0xb9a839a8},
{0xbc003c00,0xb9a839a8,0x3c00bc00,0xb9a839a8},{0xbc003c00,0xb9a839a8,0x3c00bc00,0xb9a839a8},
{0xb61f3b64,0x3872323e,0x361fbb64,0xbaa73bd9},{0x3b64b61f,0x3aa7bbd9,0xbb64361f,0x3872323e},
{0x361fbb64,0xb872b23e,0xb61f3b64,0x3aa7bbd9},{0xbb64361f,0xbaa73bd9,0x3b64b61f,0xb872b23e},
{0x39a839a8,0x3b64b61f,0xb9a8b9a8,0x361f3b64},{0xb9a8b9a8,0xbb64361f,0x39a839a8,0xb61fbb64},
{0x39a839a8,0x3b64b61f,0xb9a8b9a8,0x361f3b64},{0xb9a8b9a8,0xbb64361f,0x39a839a8,0xb61fbb64},
{0x3b64361f,0xb23ebaa7,0xbb64b61f,0x3bd93872},{0x361f3b64,0x3bd93872,0xb61fbb64,0x323e3aa7},
{0xbb64b61f,0x323e3aa7,0x3b64361f,0xbbd9b872},{0xb61fbb64,0xbbd9b872,0x361f3b64,0xb23ebaa7},
{0x0,0x0,0x0,0x3c003c00},{0x0,0x0,0x0,0x3c003c00},
{0x0,0x0,0x0,0x3c003c00},{0x0,0x0,0x0,0x3c003c00},
{0x3b64361f,0xbbd9b872,0xbb64b61f,0x323e3aa7},{0x361f3b64,0xb23ebaa7,0xb61fbb64,0xbbd9b872},
{0xbb64b61f,0x3bd93872,0x3b64361f,0xb23ebaa7},{0xb61fbb64,0x323e3aa7,0x361f3b64,0x3bd93872},
{0x39a839a8,0xb61fbb64,0xb9a8b9a8,0xbb64361f},{0xb9a8b9a8,0x361f3b64,0x39a839a8,0x3b64b61f},
{0x39a839a8,0xb61fbb64,0xb9a8b9a8,0xbb64361f},{0xb9a8b9a8,0x361f3b64,0x39a839a8,0x3b64b61f},
{0xb61f3b64,0x3aa7bbd9,0x361fbb64,0xb872b23e},{0x3b64b61f,0xb872b23e,0xbb64361f,0xbaa73bd9},
{0x361fbb64,0xbaa73bd9,0xb61f3b64,0x3872323e},{0xbb64361f,0x3872323e,0x3b64b61f,0x3aa7bbd9},
{0xbc003c00,0x39a8b9a8,0x3c00bc00,0x39a8b9a8},{0xbc003c00,0x39a8b9a8,0x3c00bc00,0x39a8b9a8},
{0xbc003c00,0x39a8b9a8,0x3c00bc00,0x39a8b9a8},{0xbc003c00,0x39a8b9a8,0x3c00bc00,0x39a8b9a8},
{0xb61f3b64,0xb872b23e,0x361fbb64,0x3aa7bbd9},{0x3b64b61f,0xbaa73bd9,0xbb64361f,0xb872b23e},
{0x361fbb64,0x3872323e,0xb61f3b64,0xbaa73bd9},{0xbb64361f,0x3aa7bbd9,0x3b64b61f,0x3872323e},
{0x39a839a8,0xbb64361f,0xb9a8b9a8,0xb61fbb64},{0xb9a8b9a8,0x3b64b61f,0x39a839a8,0x361f3b64},
{0x39a839a8,0xbb64361f,0xb9a8b9a8,0xb61fbb64},{0xb9a8b9a8,0x3b64b61f,0x39a839a8,0x361f3b64},
{0x3b64361f,0x323e3aa7,0xbb64b61f,0xbbd9b872},{0x361f3b64,0xbbd9b872,0xb61fbb64,0xb23ebaa7},
{0xbb64b61f,0xb23ebaa7,0x3b64361f,0x3bd93872},{0xb61fbb64,0x3bd93872,0x361f3b64,0x323e3aa7},
{0x34003400,0xb4003400,0x34003400,0xb4003400},{0x34003400,0xb4003400,0x34003400,0xb4003400},
{0x34003400,0xb4003400,0x34003400,0xb4003400},{0x34003400,0xb4003400,0x34003400,0xb4003400},
{0x33643400,0xb3643400,0xb364b400,0x3364b400},{0x2e1f31a8,0xae1f31a8,0xae1fb1a8,0x2e1fb1a8},
{0xae1f0000,0x2e1f0000,0x2e1f0000,0xae1f0000},{0xb364b1a8,0x3364b1a8,0x336431a8,0xb36431a8},
{0x31a83400,0xb1a83400,0x31a83400,0xb1a83400},{0xb1a80000,0x31a80000,0xb1a80000,0x31a80000},
{0xb1a8b400,0x31a8b400,0xb1a8b400,0x31a8b400},{0x31a80000,0xb1a80000,0x31a80000,0xb1a80000},
{0x2e1f3400,0xae1f3400,0xae1fb400,0x2e1fb400},{0xb364b1a8,0x3364b1a8,0x336431a8,0xb36431a8},
{0x33640000,0xb3640000,0xb3640000,0x33640000},{0xae1f31a8,0x2e1f31a8,0x2e1fb1a8,0xae1fb1a8},
{0x3400,0x3400,0x3400,0x3400},{0xb400,0xb400,0xb400,0xb400},
{0x3400,0x3400,0x3400,0x3400},{0xb400,0xb400,0xb400,0xb400},
{0xae1f3400,0x2e1f3400,0x2e1fb400,0xae1fb400},{0x3364b1a8,0xb364b1a8,0xb36431a8,0x336431a8},
{0xb3640000,0x33640000,0x33640000,0xb3640000},{0x2e1f31a8,0xae1f31a8,0xae1fb1a8,0x2e1fb1a8},
{0xb1a83400,0x31a83400,0xb1a83400,0x31a83400},{0x31a80000,0xb1a80000,0x31a80000,0xb1a80000},
{0x31a8b400,0xb1a8b400,0x31a8b400,0xb1a8b400},{0xb1a80000,0x31a80000,0xb1a80000,0x31a80000},
{0xb3643400,0x33643400,0x3364b400,0xb364b400},{0xae1f31a8,0x2e1f31a8,0x2e1fb1a8,0xae1fb1a8},
{0x2e1f0000,0xae1f0000,0xae1f0000,0x2e1f0000},{0x3364b1a8,0xb364b1a8,0xb36431a8,0x336431a8},
{0x0,0x0,0x0,0x0},{0x0,0x0,0x0,0x0},
{0x0,0x0,0x0,0x0},{0x0,0x0,0x0,0x0},
{0x2e1f0000,0xae1f0000,0xae1f0000,0x2e1f0000},{0x336431a8,0xb36431a8,0xb364b1a8,0x3364b1a8},
{0x33643400,0xb3643400,0xb364b400,0x3364b400},{0x2e1f31a8,0xae1f31a8,0xae1fb1a8,0x2e1fb1a8},
{0x31a80000,0xb1a80000,0x31a80000,0xb1a80000},{0x31a83400,0xb1a83400,0x31a83400,0xb1a83400},
{0xb1a80000,0x31a80000,0xb1a80000,0x31a80000},{0xb1a8b400,0x31a8b400,0xb1a8b400,0x31a8b400},
{0x33640000,0xb3640000,0xb3640000,0x33640000},{0xae1f31a8,0x2e1f31a8,0x2e1fb1a8,0xae1fb1a8},
{0xae1fb400,0x2e1fb400,0x2e1f3400,0xae1f3400},{0x336431a8,0xb36431a8,0xb364b1a8,0x3364b1a8},
{0x34000000,0xb4000000,0x34000000,0xb4000000},{0xb4000000,0x34000000,0xb4000000,0x34000000},
{0x34000000,0xb4000000,0x34000000,0xb4000000},{0xb4000000,0x34000000,0xb4000000,0x34000000},
{0x33640000,0xb3640000,0xb3640000,0x33640000},{0xae1fb1a8,0x2e1fb1a8,0x2e1f31a8,0xae1f31a8},
{0xae1f3400,0x2e1f3400,0x2e1fb400,0xae1fb400},{0x3364b1a8,0xb364b1a8,0xb36431a8,0x336431a8},
{0x31a80000,0xb1a80000,0x31a80000,0xb1a80000},{0x31a8b400,0xb1a8b400,0x31a8b400,0xb1a8b400},
{0xb1a80000,0x31a80000,0xb1a80000,0x31a80000},{0xb1a83400,0x31a83400,0xb1a83400,0x31a83400},
{0x2e1f0000,0xae1f0000,0xae1f0000,0x2e1f0000},{0x3364b1a8,0xb364b1a8,0xb36431a8,0x336431a8},
{0x3364b400,0xb364b400,0xb3643400,0x33643400},{0x2e1fb1a8,0xae1fb1a8,0xae1f31a8,0x2e1f31a8},
{0x80008000,0x80008000,0x80008000,0x80008000},{0x80008000,0x80008000,0x80008000,0x80008000},
{0x80008000,0x80008000,0x80008000,0x80008000},{0x80008000,0x80008000,0x80008000,0x80008000},
{0xae1f8000,0x2e1f8000,0x2e1f8000,0xae1f8000},{0xb364b1a8,0x3364b1a8,0x336431a8,0xb36431a8},
{0xb364b400,0x3364b400,0x33643400,0xb3643400},{0xae1fb1a8,0x2e1fb1a8,0x2e1f31a8,0xae1f31a8},
{0xb1a88000,0x31a88000,0xb1a88000,0x31a88000},{0xb1a8b400,0x31a8b400,0xb1a8b400,0x31a8b400},
{0x31a88000,0xb1a88000,0x31a88000,0xb1a88000},{0x31a83400,0xb1a83400,0x31a83400,0xb1a83400},
{0xb3648000,0x33648000,0x33648000,0xb3648000},{0x2e1fb1a8,0xae1fb1a8,0xae1f31a8,0x2e1f31a8},
{0x2e1f3400,0xae1f3400,0xae1fb400,0x2e1fb400},{0xb364b1a8,0x3364b1a8,0x336431a8,0xb36431a8},
{0xb4008000,0x34008000,0xb4008000,0x34008000},{0x34008000,0xb4008000,0x34008000,0xb4008000},
{0xb4008000,0x34008000,0xb4008000,0x34008000},{0x34008000,0xb4008000,0x34008000,0xb4008000},
{0xb3648000,0x33648000,0x33648000,0xb3648000},{0x2e1f31a8,0xae1f31a8,0xae1fb1a8,0x2e1fb1a8},
{0x2e1fb400,0xae1fb400,0xae1f3400,0x2e1f3400},{0xb36431a8,0x336431a8,0x3364b1a8,0xb364b1a8},
{0xb1a88000,0x31a88000,0xb1a88000,0x31a88000},{0xb1a83400,0x31a83400,0xb1a83400,0x31a83400},
{0x31a88000,0xb1a88000,0x31a88000,0xb1a88000},{0x31a8b400,0xb1a8b400,0x31a8b400,0xb1a8b400},
{0xae1f8000,0x2e1f8000,0x2e1f8000,0xae1f8000},{0xb36431a8,0x336431a8,0x3364b1a8,0xb364b1a8},
{0xb3643400,0x33643400,0x3364b400,0xb364b400},{0xae1f31a8,0x2e1f31a8,0x2e1fb1a8,0xae1fb1a8},
{0x35a835a8,0x0,0x353a35a8,0x30540000},{0x35a835a8,0x0,0x30543400,0x353a3400},
{0x35a835a8,0x0,0xb0540000,0x353a35a8},{0x35a835a8,0x0,0xb53ab400,0x30543400},
{0x35a635a8,0x24710000,0x351d35a8,0x30d60000},{0x359835a1,0x2aa42870,0x2d7f332d,0x357d345f},
{0x357d358c,0x2d7f2c6a,0xb2bdac6a,0x348b358c},{0x3554356a,0x2f9f2e92,0xb5a6b4fd,0x24713155},
{0x35a135a8,0x28700000,0x34fd35a8,0x31550000},{0x356a358c,0x2e922c6a,0x28703249,0x35a134b4},
{0x34fd353a,0x31553054,0xb45fb054,0x332d353a},{0x345f34b4,0x332d3249,0xb56ab58c,0xae922c6a},
{0x359835a8,0x2aa40000,0x34da35a8,0x31d10000},{0x351d356a,0x30d62e92,0xa4713155,0x35a634fd},
{0x343134b4,0x33993249,0xb51db249,0x30d634b4},{0x31d1332d,0x34da345f,0xb48bb5a1,0xb2bda870},
{0x358c35a8,0x2c6a0000,0x34b435a8,0x32490000},{0x34b4353a,0x32493054,0xac6a3054,0x358c353a},
{0x32493400,0x34b43400,0xb58cb400,0x2c6a3400},{0x2c6a3054,0x358c353a,0xb249b53a,0xb4b4b054},
{0x357d35a8,0x2d7f0000,0x348b35a8,0x32bd0000},{0x343134fd,0x33993155,0xaf9f2e92,0x3554356a},
{0x2f9f3249,0x355434b4,0xb5a6b4b4,0xa4713249},{0xaaa42870,0x359835a1,0xad7fb45f,0xb57db32d},
{0x356a35a8,0x2e920000,0x345f35a8,0x332d0000},{0x332d34b4,0x345f3249,0xb1552c6a,0x34fd358c},
{0x28703054,0x35a1353a,0xb56ab53a,0xae923054},{0xb155ac6a,0x34fd358c,0x2870b249,0xb5a1b4b4},
{0x355435a8,0x2f9f0000,0x343135a8,0x33990000},{0x31d1345f,0x34da332d,0xb2bd2870,0x348b35a1},
{0xaaa42c6a,0x3598358c,0xb4dab58c,0xb1d12c6a},{0xb431b155,0x339934fd,0x30d6ae92,0xb51db56a},
{0x3c003c00,0x0,0x80008000,0x3c003c00},{0x3c003c00,0x0,0x80008000,0x3c003c00},
{0x3c003c00,0x0,0x80008000,0x3c003c00},{0x3c003c00,0x0,0x80008000,0x3c003c00},
{0x39a83c00,0x39a80000,0xb9a88000,0x39a83c00},{0xb9a80000,0x39a83c00,0xb9a8bc00,0xb9a80000},
{0xb9a8bc00,0xb9a80000,0x39a88000,0xb9a8bc00},{0x39a80000,0xb9a8bc00,0x39a83c00,0x39a80000},
{0x3c00,0x3c000000,0xbc008000,0x3c00},{0xbc00,0xbc000000,0x3c008000,0xbc00},
{0x3c00,0x3c000000,0xbc008000,0x3c00},{0xbc00,0xbc000000,0x3c008000,0xbc00},
{0xb9a83c00,0x39a80000,0xb9a88000,0xb9a83c00},{0x39a80000,0x39a8bc00,0xb9a83c00,0x39a80000},
{0x39a8bc00,0xb9a80000,0x39a88000,0x39a8bc00},{0xb9a80000,0xb9a83c00,0x39a8bc00,0xb9a80000},
{0xbc003c00,0x0,0x80008000,0xbc003c00},{0xbc003c00,0x0,0x80008000,0xbc003c00},
{0xbc003c00,0x0,0x80008000,0xbc003c00},{0xbc003c00,0x0,0x80008000,0xbc003c00},
{0xb9a83c00,0xb9a80000,0x39a88000,0xb9a83c00},{0x39a80000,0xb9a83c00,0x39a8bc00,0x39a80000},
{0x39a8bc00,0x39a80000,0xb9a88000,0x39a8bc00},{0xb9a80000,0x39a8bc00,0xb9a83c00,0xb9a80000},
{0x3c00,0xbc000000,0x3c008000,0x3c00},{0xbc00,0x3c000000,0xbc008000,0xbc00},
{0x3c00,0xbc000000,0x3c008000,0x3c00},{0xbc00,0x3c000000,0xbc008000,0xbc00},
{0x39a83c00,0xb9a80000,0x39a88000,0x39a83c00},{0xb9a80000,0xb9a8bc00,0x39a83c00,0xb9a80000},
{0xb9a8bc00,0x39a80000,0xb9a88000,0xb9a8bc00},{0x39a80000,0x39a83c00,0xb9a8bc00,0x39a80000},
{0x3f803f80,0x0,0x80008000,0x3f803f80},{0x3f803f80,0x0,0x80008000,0x3f803f80},
{0x3f803f80,0x0,0x80008000,0x3f803f80},{0x3f803f80,0x0,0x80008000,0x3f803f80},
{0x3f353f80,0x3f350000,0xbf358000,0x3f353f80},{0xbf350000,0x3f353f80,0xbf35bf80,0xbf350000},
{0xbf35bf80,0xbf350000,0x3f358000,0xbf35bf80},{0x3f350000,0xbf35bf80,0x3f353f80,0x3f350000},
{0x3f80,0x3f800000,0xbf808000,0x3f80},{0xbf80,0xbf800000,0x3f808000,0xbf80},
{0x3f80,0x3f800000,0xbf808000,0x3f80},{0xbf80,0xbf800000,0x3f808000,0xbf80},
{0xbf353f80,0x3f350000,0xbf358000,0xbf353f80},{0x3f350000,0x3f35bf80,0xbf353f80,0x3f350000},
{0x3f35bf80,0xbf350000,0x3f358000,0x3f35bf80},{0xbf350000,0xbf353f80,0x3f35bf80,0xbf350000},
{0xbf803f80,0x0,0x80008000,0xbf803f80},{0xbf803f80,0x0,0x80008000,0xbf803f80},
{0xbf803f80,0x0,0x80008000,0xbf803f80},{0xbf803f80,0x0,0x80008000,0xbf803f80},
{0xbf353f80,0xbf350000,0x3f358000,0xbf353f80},{0x3f350000,0xbf353f80,0x3f35bf80,0x3f350000},
{0x3f35bf80,0x3f350000,0xbf358000,0x3f35bf80},{0xbf350000,0x3f35bf80,0xbf353f80,0xbf350000},
{0x3f80,0xbf800000,0x3f808000,0x3f80},{0xbf80,0x3f800000,0xbf808000,0xbf80},
{0x3f80,0xbf800000,0x3f808000,0x3f80},{0xbf80,0x3f800000,0xbf808000,0xbf80},
{0x3f353f80,0xbf350000,0x3f358000,0x3f353f80},{0xbf350000,0xbf35bf80,0x3f353f80,0xbf350000},
{0xbf35bf80,0x3f350000,0xbf358000,0xbf35bf80},{0x3f350000,0x3f353f80,0xbf35bf80,0x3f350000},
{0x3eb504f3,0x0,0x3eb504f3,0x0},{0x3eb504f3,0x0,0x3eb504f3,0x0},
{0x3eb504f3,0x0,0x3eb504f3,0x0},{0x3eb504f3,0x0,0x3eb504f3,0x0},
{0x3eb504f3,0x0,0x3eb4cd21,0x3c8e1d7b},{0x3eb425ce,0x3d0df1a9,0x3eb30f61,0x3d547d09},
{0x3eb18a86,0x3d8d42af,0x3eaf982b,0x3dafefbb},{0x3ead3986,0x3dd23045,0x3eaa700c,0x3df3ef2f},
{0x3eb504f3,0x0,0x3eb425ce,0x3d0df1a9},{0x3eb18a86,0x3d8d42af,0x3ead3986,0x3dd23045},
{0x3ea73d75,0x3e0a8bd4,0x3e9fa512,0x3e2aa9f2},{0x3e968317,0x3e49234e,0x3e8bee0a,0x3e65acc6},
{0x3eb504f3,0x0,0x3eb30f61,0x3d547d09},{0x3ead3986,0x3dd23045,0x3ea3a3b9,0x3e1aca9e},
{0x3e968317,0x3e49234e,0x3e862061,0x3e73215c},{0x3e65acc6,0x3e8bee0a,0x3e3a2005,0x3e9b43f5},
{0x3eb504f3,0x0,0x3eb18a86,0x3d8d42af},{0x3ea73d75,0x3e0a8bd4,0x3e968317,0x3e49234e},
{0x3e800000,0x3e800000,0x3e49234e,0x3e968317},{0x3e0a8bd4,0x3ea73d75,0x3d8d42af,0x3eb18a86},
{0x3eb504f3,0x0,0x3eaf982b,0x3dafefbb},{0x3e9fa512,0x3e2aa9f2,0x3e862061,0x3e73215c},
{0x3e49234e,0x3e968317,0x3df3ef2f,0x3eaa700c},{0x3d0df1a9,0x3eb425ce,0xbd547d09,0x3eb30f61},
{0x3eb504f3,0x0,0x3ead3986,0x3dd23045},{0x3e968317,0x3e49234e,0x3e65acc6,0x3e8bee0a},
{0x3e0a8bd4,0x3ea73d75,0x3d0df1a9,0x3eb425ce},{0xbd8d42af,0x3eb18a86,0xbe2aa9f2,0x3e9fa512},
{0x3eb504f3,0x0,0x3eaa700c,0x3df3ef2f},{0x3e8bee0a,0x3e65acc6,0x3e3a2005,0x3e9b43f5},
{0x3d8d42af,0x3eb18a86,0xbd547d09,0x3eb30f61},{0xbe2aa9f2,0x3e9fa512,0xbe862061,0x3e73215c},
{0x3eb504f3,0x0,0x3eb504f3,0x0},{0x3eb504f3,0x0,0x3eb504f3,0x0},
{0x3eb504f3,0x0,0x3eb504f3,0x0},{0x3eb504f3,0x0,0x3eb504f3,0x0},
{0x3ea73d75,0x3e0a8bd4,0x3ea3a3b9,0x3e1aca9e},{0x3e9fa512,0x3e2aa9f2,0x3e9b43f5,0x3e3a2005},
{0x3e968317,0x3e49234e,0x3e916566,0x3e57aa8b},{0x3e8bee0a,0x3e65acc6,0x3e862061,0x3e73215c},
{0x3e800000,0x3e800000,0x3e65acc6,0x3e8bee0a},{0x3e49234e,0x3e968317,0x3e2aa9f2,0x3e9fa512},
{0x3e0a8bd4,0x3ea73d75,0x3dd23045,0x3ead3986},{0x3d8d42af,0x3eb18a86,0x3d0df1a9,0x3eb425ce},
{0x3e0a8bd4,0x3ea73d75,0x3dafefbb,0x3eaf982b},{0x3d0df1a9,0x3eb425ce,0xbc8e1d7b,0x3eb4cd21},
{0xbd8d42af,0x3eb18a86,0xbdf3ef2f,0x3eaa700c},{0xbe2aa9f2,0x3e9fa512,0xbe57aa8b,0x3e916566},
{0x0,0x3eb504f3,0xbd8d42af,0x3eb18a86},{0xbe0a8bd4,0x3ea73d75,0xbe49234e,0x3e968317},
{0xbe800000,0x3e800000,0xbe968317,0x3e49234e},{0xbea73d75,0x3e0a8bd4,0xbeb18a86,0x3d8d42af},
{0xbe0a8bd4,0x3ea73d75,0xbe57aa8b,0x3e916566},{0xbe8bee0a,0x3e65acc6,0xbea3a3b9,0x3e1aca9e},
{0xbeb18a86,0x3d8d42af,0xbeb4cd21,0xbc8e1d7b},{0xbead3986,0xbdd23045,0xbe9b43f5,0xbe3a2005},
{0xbe800000,0x3e800000,0xbe9fa512,0x3e2aa9f2},{0xbeb18a86,0x3d8d42af,0xbeb425ce,0xbd0df1a9},
{0xbea73d75,0xbe0a8bd4,0xbe8bee0a,0xbe65acc6},{0xbe49234e,0xbe968317,0xbdd23045,0xbead3986},
{0xbea73d75,0x3e0a8bd4,0xbeb4cd21,0x3c8e1d7b},{0xbead3986,0xbdd23045,0xbe916566,0xbe57aa8b},
{0xbe49234e,0xbe968317,0xbdafefbb,0xbeaf982b},{0x3d0df1a9,0xbeb425ce,0x3e1aca9e,0xbea3a3b9},
{0x3e803e80,0xbe803e80,0x3e803e80,0xbe803e80},{0x3e803e80,0xbe803e80,0x3e803e80,0xbe803e80},
{0x3e803e80,0xbe803e80,0x3e803e80,0xbe803e80},{0x3e803e80,0xbe803e80,0x3e803e80,0xbe803e80},
{0x3e6d3e80,0xbe6d3e80,0xbe6dbe80,0x3e6dbe80},{0x3dc43e35,0xbdc43e35,0xbdc4be35,0x3dc4be35},
{0xbdc40000,0x3dc40000,0x3dc40000,0xbdc40000},{0xbe6dbe35,0x3e6dbe35,0x3e6d3e35,0xbe6d3e35},
{0x3e353e80,0xbe353e80,0x3e353e80,0xbe353e80},{0xbe350000,0x3e350000,0xbe350000,0x3e350000},
{0xbe35be80,0x3e35be80,0xbe35be80,0x3e35be80},{0x3e350000,0xbe350000,0x3e350000,0xbe350000},
{0x3dc43e80,0xbdc43e80,0xbdc4be80,0x3dc4be80},{0xbe6dbe35,0x3e6dbe35,0x3e6d3e35,0xbe6d3e35},
{0x3e6d0000,0xbe6d0000,0xbe6d0000,0x3e6d0000},{0xbdc43e35,0x3dc43e35,0x3dc4be35,0xbdc4be35},
{0x3e80,0x3e80,0x3e80,0x3e80},{0xbe80,0xbe80,0xbe80,0xbe80},
{0x3e80,0x3e80,0x3e80,0x3e80},{0xbe80,0xbe80,0xbe80,0xbe80},
{0xbdc43e80,0x3dc43e80,0x3dc4be80,0xbdc4be80},{0x3e6dbe35,0xbe6dbe35,0xbe6d3e35,0x3e6d3e35},
{0xbe6d0000,0x3e6d0000,0x3e6d0000,0xbe6d0000},{0x3dc43e35,0xbdc43e35,0xbdc4be35,0x3dc4be35},
{0xbe353e80,0x3e353e80,0xbe353e80,0x3e353e80},{0x3e350000,0xbe350000,0x3e350000,0xbe350000},
{0x3e35be80,0xbe35be80,0x3e35be80,0xbe35be80},{0xbe350000,0x3e350000,0xbe350000,0x3e350000},
{0xbe6d3e80,0x3e6d3e80,0x3e6dbe80,0xbe6dbe80},{0xbdc43e35,0x3dc43e35,0x3dc4be35,0xbdc4be35},
{0x3dc40000,0xbdc40000,0xbdc40000,0x3dc40000},{0x3e6dbe35,0xbe6dbe35,0xbe6d3e35,0x3e6d3e35},
{0x0,0x0,0x0,0x0},{0x0,0x0,0x0,0x0},
{0x0,0x0,0x0,0x0},{0x0,0x0,0x0,0x0},
{0x3dc40000,0xbdc40000,0xbdc40000,0x3dc40000},{0x3e6d3e35,0xbe6d3e35,0xbe6dbe35,0x3e6dbe35},
{0x3e6d3e80,0xbe6d3e80,0xbe6dbe80,0x3e6dbe80},{0x3dc43e35,0xbdc43e35,0xbdc4be35,0x3dc4be35},
{0x3e350000,0xbe350000,0x3e350000,0xbe350000},{0x3e353e80,0xbe353e80,0x3e353e80,0xbe353e80},
{0xbe350000,0x3e350000,0xbe350000,0x3e350000},{0xbe35be80,0x3e35be80,0xbe35be80,0x3e35be80},
{0x3e6d0000,0xbe6d0000,0xbe6d0000,0x3e6d0000},{0xbdc43e35,0x3dc43e35,0x3dc4be35,0xbdc4be35},
{0xbdc4be80,0x3dc4be80,0x3dc43e80,0xbdc43e80},{0x3e6d3e35,0xbe6d3e35,0xbe6dbe35,0x3e6dbe35},
{0x3e800000,0xbe800000,0x3e800000,0xbe800000},{0xbe800000,0x3e800000,0xbe800000,0x3e800000},
{0x3e800000,0xbe800000,0x3e800000,0xbe800000},{0xbe800000,0x3e800000,0xbe800000,0x3e800000},
{0x3e6d0000,0xbe6d0000,0xbe6d0000,0x3e6d0000},{0xbdc4be35,0x3dc4be35,0x3dc43e35,0xbdc43e35},
{0xbdc43e80,0x3dc43e80,0x3dc4be80,0xbdc4be80},{0x3e6dbe35,0xbe6dbe35,0xbe6d3e35,0x3e6d3e35},
{0x3e350000,0xbe350000,0x3e350000,0xbe350000},{0x3e35be80,0xbe35be80,0x3e35be80,0xbe35be80},
{0xbe350000,0x3e350000,0xbe350000,0x3e350000},{0xbe353e80,0x3e353e80,0xbe353e80,0x3e353e80},
{0x3dc40000,0xbdc40000,0xbdc40000,0x3dc40000},{0x3e6dbe35,0xbe6dbe35,0xbe6d3e35,0x3e6d3e35},
{0x3e6dbe80,0xbe6dbe80,0xbe6d3e80,0x3e6d3e80},{0x3dc4be35,0xbdc4be35,0xbdc43e35,0x3dc43e35},
{0x80008000,0x80008000,0x80008000,0x80008000},{0x80008000,0x80008000,0x80008000,0x80008000},
{0x80008000,0x80008000,0x80008000,0x80008000},{0x80008000,0x80008000,0x80008000,0x80008000},
{0xbdc48000,0x3dc48000,0x3dc48000,0xbdc48000},{0xbe6dbe35,0x3e6dbe35,0x3e6d3e35,0xbe6d3e35},
{0xbe6dbe80,0x3e6dbe80,0x3e6d3e80,0xbe6d3e80},{0xbdc4be35,0x3dc4be35,0x3dc43e35,0xbdc43e35},
{0xbe358000,0x3e358000,0xbe358000,0x3e358000},{0xbe35be80,0x3e35be80,0xbe35be80,0x3e35be80},
{0x3e358000,0xbe358000,0x3e358000,0xbe358000},{0x3e353e80,0xbe353e80,0x3e353e80,0xbe353e80},
{0xbe6d8000,0x3e6d8000,0x3e6d8000,0xbe6d8000},{0x3dc4be35,0xbdc4be35,0xbdc43e35,0x3dc43e35},
{0x3dc43e80,0xbdc43e80,0xbdc4be80,0x3dc4be80},{0xbe6dbe35,0x3e6dbe35,0x3e6d3e35,0xbe6d3e35},
{0xbe808000,0x3e808000,0xbe808000,0x3e808000},{0x3e808000,0xbe808000,0x3e808000,0xbe808000},
{0xbe808000,0x3e808000,0xbe808000,0x3e808000},{0x3e808000,0xbe808000,0x3e808000,0xbe808000},
{0xbe6d8000,0x3e6d8000,0x3e6d8000,0xbe6d8000},{0x3dc43e35,0xbdc43e35,0xbdc4be35,0x3dc4be35},
{0x3dc4be80,0xbdc4be80,0xbdc43e80,0x3dc43e80},{0xbe6d3e35,0x3e6d3e35,0x3e6dbe35,0xbe6dbe35},
{0xbe358000,0x3e358000,0xbe358000,0x3e358000},{0xbe353e80,0x3e353e80,0xbe353e80,0x3e353e80},
{0x3e358000,0xbe358000,0x3e358000,0xbe358000},{0x3e35be80,0xbe35be80,0x3e35be80,0xbe35be80},
{0xbdc48000,0x3dc48000,0x3dc48000,0xbdc48000},{0xbe6d3e35,0x3e6d3e35,0x3e6dbe35,0xbe6dbe35},
{0xbe6d3e80,0x3e6d3e80,0x3e6dbe80,0xbe6dbe80},{0xbdc43e35,0x3dc43e35,0x3dc4be35,0xbdc4be35},
{0x3f803f80,0x3f7b3f80,0x3f803f80,0xbe480000},{0x3f803f80,0x3f553f6d,0x3f803f80,0xbf0ebec4},
{0x3f803f80,0x3f0e3f35,0x3f803f80,0xbf55bf35},{0x3f803f80,0x3e483ec4,0x3f803f80,0xbf7bbf6d},
{0x3f353f80,0x3f0e3f80,0x3f353f80,0xbf550000},{0xbf350000,0xbf7bbec4,0xbf350000,0xbe48bf6d},
{0xbf35bf80,0x3e48bf35,0xbf35bf80,0x3f7b3f35},{0x3f350000,0x3f553f6d,0x3f350000,0xbf0e3ec4},
{0x3f80,0xbe483f80,0x3f80,0xbf7b0000},{0xbf80,0x3f0ebf6d,0xbf80,0x3f553ec4},
{0x3f80,0xbf553f35,0x3f80,0xbf0ebf35},{0xbf80,0x3f7bbec4,0xbf80,0x3e483f6d},
{0xbf353f80,0xbf553f80,0xbf353f80,0xbf0e0000},{0x3f350000,0x3e483ec4,0x3f350000,0xbf7b3f6d},
{0x3f35bf80,0x3f7bbf35,0x3f35bf80,0xbe483f35},{0xbf350000,0x3f0ebf6d,0xbf350000,0x3f55bec4},
{0xbf803f80,0xbf7b3f80,0xbf803f80,0x3e480000},{0xbf803f80,0xbf553f6d,0xbf803f80,0x3f0ebec4},
{0xbf803f80,0xbf0e3f35,0xbf803f80,0x3f55bf35},{0xbf803f80,0xbe483ec4,0xbf803f80,0x3f7bbf6d},
{0xbf353f80,0xbf0e3f80,0xbf353f80,0x3f550000},{0x3f350000,0x3f7bbec4,0x3f350000,0x3e48bf6d},
{0x3f35bf80,0xbe48bf35,0x3f35bf80,0xbf7b3f35},{0xbf350000,0xbf553f6d,0xbf350000,0x3f0e3ec4},
{0x3f80,0x3e483f80,0x3f80,0x3f7b0000},{0xbf80,0xbf0ebf6d,0xbf80,0xbf553ec4},
{0x3f80,0x3f553f35,0x3f80,0x3f0ebf35},{0xbf80,0xbf7bbec4,0xbf80,0xbe483f6d},
{0x3f353f80,0x3f553f80,0x3f353f80,0x3f0e0000},{0xbf350000,0xbe483ec4,0xbf350000,0x3f7b3f6d},
{0xbf35bf80,0xbf7bbf35,0xbf35bf80,0x3e483f35},{0x3f350000,0xbf0ebf6d,0x3f350000,0xbf55bec4},
{0x3f803f80,0xbf7bbf80,0x3f803f80,0x3e480000},{0x3f803f80,0xbf55bf6d,0x3f803f80,0x3f0e3ec4},
{0x3f803f80,0xbf0ebf35,0x3f803f80,0x3f553f35},{0x3f803f80,0xbe48bec4,0x3f803f80,0x3f7b3f6d},
{0x3f353f80,0xbf0ebf80,0x3f353f80,0x3f550000},{0xbf350000,0x3f7b3ec4,0xbf350000,0x3e483f6d},
{0xbf35bf80,0xbe483f35,0xbf35bf80,0xbf7bbf35},{0x3f350000,0xbf55bf6d,0x3f350000,0x3f0ebec4},
{0x3f80,0x3e48bf80,0x3f80,0x3f7b0000},{0xbf80,0xbf0e3f6d,0xbf80,0xbf55bec4},
{0x3f80,0x3f55bf35,0x3f80,0x3f0e3f35},{0xbf80,0xbf7b3ec4,0xbf80,0xbe48bf6d},
{0xbf353f80,0x3f55bf80,0xbf353f80,0x3f0e0000},{0x3f350000,0xbe48bec4,0x3f350000,0x3f7bbf6d},
{0x3f35bf80,0xbf7b3f35,0x3f35bf80,0x3e48bf35},{0xbf350000,0xbf0e3f6d,0xbf350000,0xbf553ec4},
{0xbf803f80,0x3f7bbf80,0xbf803f80,0xbe480000},{0xbf803f80,0x3f55bf6d,0xbf803f80,0xbf0e3ec4},
{0xbf803f80,0x3f0ebf35,0xbf803f80,0xbf553f35},{0xbf803f80,0x3e48bec4,0xbf803f80,0xbf7b3f6d},
{0xbf353f80,0x3f0ebf80,0xbf353f80,0xbf550000},{0x3f350000,0xbf7b3ec4,0x3f350000,0xbe483f6d},
{0x3f35bf80,0x3e483f35,0x3f35bf80,0x3f7bbf35},{0xbf350000,0x3f55bf6d,0xbf350000,0xbf0ebec4},
{0x3f80,0xbe48bf80,0x3f80,0xbf7b0000},{0xbf80,0x3f0e3f6d,0xbf80,0x3f55bec4},
{0x3f80,0xbf55bf35,0x3f80,0xbf0e3f35},{0xbf80,0x3f7b3ec4,0xbf80,0x3e48bf6d},
{0x3f353f80,0xbf55bf80,0x3f353f80,0xbf0e0000},{0xbf350000,0x3e48bec4,0xbf350000,0xbf7bbf6d},
{0xbf35bf80,0x3f7b3f35,0xbf35bf80,0xbe48bf35},{0x3f350000,0x3f0e3f6d,0x3f350000,0x3f553ec4},
{0x3f6d3f80,0x3f553f80,0xbf6dbf80,0x3f0e0000},{0x3ec43f35,0xbe483ec4,0xbec4bf35,0x3f7b3f6d},
{0xbec40000,0xbf7bbf35,0x3ec40000,0x3e483f35},{0xbf6dbf35,0xbf0ebf6d,0x3f6d3f35,0xbf55bec4},
{0x3ec43f80,0x3e483f80,0xbec4bf80,0x3f7b0000},{0xbf6dbf35,0xbf0ebf6d,0x3f6d3f35,0xbf553ec4},
{0x3f6d0000,0x3f553f35,0xbf6d0000,0x3f0ebf35},{0xbec43f35,0xbf7bbec4,0x3ec4bf35,0xbe483f6d},
{0xbec43f80,0xbf0e3f80,0x3ec4bf80,0x3f550000},{0x3f6dbf35,0x3f7bbec4,0xbf6d3f35,0x3e48bf6d},
{0xbf6d0000,0xbe48bf35,0x3f6d0000,0xbf7b3f35},{0x3ec43f35,0xbf553f6d,0xbec4bf35,0x3f0e3ec4},
{0xbf6d3f80,0xbf7b3f80,0x3f6dbf80,0x3e480000},{0xbec43f35,0xbf553f6d,0x3ec4bf35,0x3f0ebec4},
{0x3ec40000,0xbf0e3f35,0xbec40000,0x3f55bf35},{0x3f6dbf35,0xbe483ec4,0xbf6d3f35,0x3f7bbf6d},
{0xbf6d3f80,0xbf553f80,0x3f6dbf80,0xbf0e0000},{0xbec43f35,0x3e483ec4,0x3ec4bf35,0xbf7b3f6d},
{0x3ec40000,0x3f7bbf35,0xbec40000,0xbe483f35},{0x3f6dbf35,0x3f0ebf6d,0xbf6d3f35,0x3f55bec4},
{0xbec43f80,0xbe483f80,0x3ec4bf80,0xbf7b0000},{0x3f6dbf35,0x3f0ebf6d,0xbf6d3f35,0x3f553ec4},
{0xbf6d0000,0xbf553f35,0x3f6d0000,0xbf0ebf35},{0x3ec43f35,0x3f7bbec4,0xbec4bf35,0x3e483f6d},
{0x3ec43f80,0x3f0e3f80,0xbec4bf80,0xbf550000},{0xbf6dbf35,0xbf7bbec4,0x3f6d3f35,0xbe48bf6d},
{0x3f6d0000,0x3e48bf35,0xbf6d0000,0x3f7b3f35},{0xbec43f35,0x3f553f6d,0x3ec4bf35,0xbf0e3ec4},
{0x3f6d3f80,0x3f7b3f80,0xbf6dbf80,0xbe480000},{0x3ec43f35,0x3f553f6d,0xbec4bf35,0xbf0ebec4},
{0xbec40000,0x3f0e3f35,0x3ec40000,0xbf55bf35},{0xbf6dbf35,0x3e483ec4,0x3f6d3f35,0xbf7bbf6d},
{0x3f6d3f80,0xbf55bf80,0xbf6dbf80,0xbf0e0000},{0x3ec43f35,0x3e48bec4,0xbec4bf35,0xbf7bbf6d},
{0xbec40000,0x3f7b3f35,0x3ec40000,0xbe48bf35},{0xbf6dbf35,0x3f0e3f6d,0x3f6d3f35,0x3f553ec4},
{0x3ec43f80,0xbe48bf80,0xbec4bf80,0xbf7b0000},{0xbf6dbf35,0x3f0e3f6d,0x3f6d3f35,0x3f55bec4},
{0x3f6d0000,0xbf55bf35,0xbf6d0000,0xbf0e3f35},{0xbec43f35,0x3f7b3ec4,0x3ec4bf35,0x3e48bf6d},
{0xbec43f80,0x3f0ebf80,0x3ec4bf80,0xbf550000},{0x3f6dbf35,0xbf7b3ec4,0xbf6d3f35,0xbe483f6d},
{0xbf6d0000,0x3e483f35,0x3f6d0000,0x3f7bbf35},{0x3ec43f35,0x3f55bf6d,0xbec4bf35,0xbf0ebec4},
{0xbf6d3f80,0x3f7bbf80,0x3f6dbf80,0xbe480000},{0xbec43f35,0x3f55bf6d,0x3ec4bf35,0xbf0e3ec4},
{0x3ec40000,0x3f0ebf35,0xbec40000,0xbf553f35},{0x3f6dbf35,0x3e48bec4,0xbf6d3f35,0xbf7b3f6d},
{0xbf6d3f80,0x3f55bf80,0x3f6dbf80,0x3f0e0000},{0xbec43f35,0xbe48bec4,0x3ec4bf35,0x3f7bbf6d},
{0x3ec40000,0xbf7b3f35,0xbec40000,0x3e48bf35},{0x3f6dbf35,0xbf0e3f6d,0xbf6d3f35,0xbf553ec4},
{0xbec43f80,0x3e48bf80,0x3ec4bf80,0x3f7b0000},{0x3f6dbf35,0xbf0e3f6d,0xbf6d3f35,0xbf55bec4},
{0xbf6d0000,0x3f55bf35,0x3f6d0000,0x3f0e3f35},{0x3ec43f35,0xbf7b3ec4,0xbec4bf35,0xbe48bf6d},
{0x3ec43f80,0xbf0ebf80,0xbec4bf80,0x3f550000},{0xbf6dbf35,0x3f7b3ec4,0x3f6d3f35,0x3e483f6d},
{0x3f6d0000,0xbe483f35,0xbf6d0000,0xbf7bbf35},{0xbec43f35,0xbf55bf6d,0x3ec4bf35,0x3f0ebec4},
{0x3f6d3f80,0xbf7bbf80,0xbf6dbf80,0x3e480000},{0x3ec43f35,0xbf55bf6d,0xbec4bf35,0x3f0e3ec4},
{0xbec40000,0xbf0ebf35,0x3ec40000,0x3f553f35},{0xbf6dbf35,0xbe48bec4,0x3f6d3f35,0x3f7b3f6d},
{0x0,0x3e480000,0x0,0x3f7b3f80},{0x0,0x3f0e3ec4,0x0,0x3f553f6d},
{0x0,0x3f553f35,0x0,0x3f0e3f35},{0x0,0x3f7b3f6d,0x0,0x3e483ec4},
{0x3f350000,0x3f550000,0x3f350000,0x3f0e3f80},{0x3f353f80,0x3e483f6d,0x3f353f80,0xbf7bbec4},
{0xbf350000,0xbf7bbf35,0xbf350000,0x3e48bf35},{0xbf35bf80,0x3f0ebec4,0xbf35bf80,0x3f553f6d},
{0x3f800000,0x3f7b0000,0x3f800000,0xbe483f80},{0xbf800000,0xbf55bec4,0xbf800000,0x3f0ebf6d},
{0x3f800000,0x3f0e3f35,0x3f800000,0xbf553f35},{0xbf800000,0xbe48bf6d,0xbf800000,0x3f7bbec4},
{0x3f350000,0x3f0e0000,0x3f350000,0xbf553f80},{0x3f35bf80,0x3f7bbf6d,0x3f35bf80,0x3e483ec4},
{0xbf350000,0x3e48bf35,0xbf350000,0x3f7bbf35},{0xbf353f80,0xbf553ec4,0xbf353f80,0x3f0ebf6d},
{0x0,0xbe480000,0x0,0xbf7b3f80},{0x0,0xbf0e3ec4,0x0,0xbf553f6d},
{0x0,0xbf553f35,0x0,0xbf0e3f35},{0x0,0xbf7b3f6d,0x0,0xbe483ec4},
{0xbf350000,0xbf550000,0xbf350000,0xbf0e3f80},{0xbf353f80,0xbe483f6d,0xbf353f80,0x3f7bbec4},
{0x3f350000,0x3f7bbf35,0x3f350000,0xbe48bf35},{0x3f35bf80,0xbf0ebec4,0x3f35bf80,0xbf553f6d},
{0xbf800000,0xbf7b0000,0xbf800000,0x3e483f80},{0x3f800000,0x3f55bec4,0x3f800000,0xbf0ebf6d},
{0xbf800000,0xbf0e3f35,0xbf800000,0x3f553f35},{0x3f800000,0x3e48bf6d,0x3f800000,0xbf7bbec4},
{0xbf350000,0xbf0e0000,0xbf350000,0x3f553f80},{0xbf35bf80,0xbf7bbf6d,0xbf35bf80,0xbe483ec4},
{0x3f350000,0xbe48bf35,0x3f350000,0xbf7bbf35},{0x3f353f80,0x3f553ec4,0x3f353f80,0xbf0ebf6d},
{0x0,0xbe480000,0x0,0xbf7bbf80},{0x0,0xbf0ebec4,0x0,0xbf55bf6d},
{0x0,0xbf55bf35,0x0,0xbf0ebf35},{0x0,0xbf7bbf6d,0x0,0xbe48bec4},
{0x3f350000,0xbf550000,0x3f350000,0xbf0ebf80},{0x3f353f80,0xbe48bf6d,0x3f353f80,0x3f7b3ec4},
{0xbf350000,0x3f7b3f35,0xbf350000,0xbe483f35},{0xbf35bf80,0xbf0e3ec4,0xbf35bf80,0xbf55bf6d},
{0x3f800000,0xbf7b0000,0x3f800000,0x3e48bf80},{0xbf800000,0x3f553ec4,0xbf800000,0xbf0e3f6d},
{0x3f800000,0xbf0ebf35,0x3f800000,0x3f55bf35},{0xbf800000,0x3e483f6d,0xbf800000,0xbf7b3ec4},
{0x3f350000,0xbf0e0000,0x3f350000,0x3f55bf80},{0x3f35bf80,0xbf7b3f6d,0x3f35bf80,0xbe48bec4},
{0xbf350000,0xbe483f35,0xbf350000,0xbf7b3f35},{0xbf353f80,0x3f55bec4,0xbf353f80,0xbf0e3f6d},
{0x0,0x3e480000,0x0,0x3f7bbf80},{0x0,0x3f0ebec4,0x0,0x3f55bf6d},
{0x0,0x3f55bf35,0x0,0x3f0ebf35},{0x0,0x3f7bbf6d,0x0,0x3e48bec4},
{0xbf350000,0x3f550000,0xbf350000,0x3f0ebf80},{0xbf353f80,0x3e48bf6d,0xbf353f80,0xbf7b3ec4},
{0x3f350000,0xbf7b3f35,0x3f350000,0x3e483f35},{0x3f35bf80,0x3f0e3ec4,0x3f35bf80,0x3f55bf6d},
{0xbf800000,0x3f7b0000,0xbf800000,0xbe48bf80},{0x3f800000,0xbf553ec4,0x3f800000,0x3f0e3f6d},
{0xbf800000,0x3f0ebf35,0xbf800000,0xbf55bf35},{0x3f800000,0xbe483f6d,0x3f800000,0x3f7b3ec4},
{0xbf350000,0x3f0e0000,0xbf350000,0xbf55bf80},{0xbf35bf80,0x3f7b3f6d,0xbf35bf80,0x3e48bec4},
{0x3f350000,0x3e483f35,0x3f350000,0x3f7b3f35},{0x3f353f80,0xbf55bec4,0x3f353f80,0x3f0e3f6d},
{0x3ec40000,0x3f0e0000,0xbec40000,0xbf55bf80},{0x3f6d3f35,0x3f7b3f6d,0xbf6dbf35,0x3e48bec4},
{0x3f6d3f80,0x3e483f35,0xbf6dbf80,0x3f7b3f35},{0x3ec43f35,0xbf55bec4,0xbec4bf35,0x3f0e3f6d},
{0x3f6d0000,0x3f7b0000,0xbf6d0000,0xbe48bf80},{0xbec43f35,0xbf553ec4,0x3ec4bf35,0x3f0e3f6d},
{0xbec4bf80,0x3f0ebf35,0x3ec43f80,0xbf55bf35},{0x3f6d3f35,0xbe483f6d,0xbf6dbf35,0x3f7b3ec4},
{0x3f6d0000,0x3f550000,0xbf6d0000,0x3f0ebf80},{0xbec4bf35,0x3e48bf6d,0x3ec43f35,0xbf7b3ec4},
{0xbec43f80,0xbf7b3f35,0x3ec4bf80,0x3e483f35},{0x3f6dbf35,0x3f0e3ec4,0xbf6d3f35,0x3f55bf6d},
{0x3ec40000,0x3e480000,0xbec40000,0x3f7bbf80},{0x3f6dbf35,0x3f0ebec4,0xbf6d3f35,0x3f55bf6d},
{0x3f6dbf80,0x3f55bf35,0xbf6d3f80,0x3f0ebf35},{0x3ec4bf35,0x3f7bbf6d,0xbec43f35,0x3e48bec4},
{0xbec40000,0xbf0e0000,0x3ec40000,0x3f55bf80},{0xbf6d3f35,0xbf7b3f6d,0x3f6dbf35,0xbe48bec4},
{0xbf6d3f80,0xbe483f35,0x3f6dbf80,0xbf7b3f35},{0xbec43f35,0x3f55bec4,0x3ec4bf35,0xbf0e3f6d},
{0xbf6d0000,0xbf7b0000,0x3f6d0000,0x3e48bf80},{0x3ec43f35,0x3f553ec4,0xbec4bf35,0xbf0e3f6d},
{0x3ec4bf80,0xbf0ebf35,0xbec43f80,0x3f55bf35},{0xbf6d3f35,0x3e483f6d,0x3f6dbf35,0xbf7b3ec4},
{0xbf6d0000,0xbf550000,0x3f6d0000,0xbf0ebf80},{0x3ec4bf35,0xbe48bf6d,0xbec43f35,0x3f7b3ec4},
{0x3ec43f80,0x3f7b3f35,0xbec4bf80,0xbe483f35},{0xbf6dbf35,0xbf0e3ec4,0x3f6d3f35,0xbf55bf6d},
{0xbec40000,0xbe480000,0x3ec40000,0xbf7bbf80},{0xbf6dbf35,0xbf0ebec4,0x3f6d3f35,0xbf55bf6d},
{0xbf6dbf80,0xbf55bf35,0x3f6d3f80,0xbf0ebf35},{0xbec4bf35,0xbf7bbf6d,0x3ec43f35,0xbe48bec4},
{0x3ec40000,0xbf0e0000,0xbec40000,0x3f553f80},{0x3f6d3f35,0xbf7bbf6d,0xbf6dbf35,0xbe483ec4},
{0x3f6d3f80,0xbe48bf35,0xbf6dbf80,0xbf7bbf35},{0x3ec43f35,0x3f553ec4,0xbec4bf35,0xbf0ebf6d},
{0x3f6d0000,0xbf7b0000,0xbf6d0000,0x3e483f80},{0xbec43f35,0x3f55bec4,0x3ec4bf35,0xbf0ebf6d},
{0xbec4bf80,0xbf0e3f35,0x3ec43f80,0x3f553f35},{0x3f6d3f35,0x3e48bf6d,0xbf6dbf35,0xbf7bbec4},
{0x3f6d0000,0xbf550000,0xbf6d0000,0xbf0e3f80},{0xbec4bf35,0xbe483f6d,0x3ec43f35,0x3f7bbec4},
{0xbec43f80,0x3f7bbf35,0x3ec4bf80,0xbe48bf35},{0x3f6dbf35,0xbf0ebec4,0xbf6d3f35,0xbf553f6d},
{0x3ec40000,0xbe480000,0xbec40000,0xbf7b3f80},{0x3f6dbf35,0xbf0e3ec4,0xbf6d3f35,0xbf553f6d},
{0x3f6dbf80,0xbf553f35,0xbf6d3f80,0xbf0e3f35},{0x3ec4bf35,0xbf7b3f6d,0xbec43f35,0xbe483ec4},
{0xbec40000,0x3f0e0000,0x3ec40000,0xbf553f80},{0xbf6d3f35,0x3f7bbf6d,0x3f6dbf35,0x3e483ec4},
{0xbf6d3f80,0x3e48bf35,0x3f6dbf80,0x3f7bbf35},{0xbec43f35,0xbf553ec4,0x3ec4bf35,0x3f0ebf6d},
{0xbf6d0000,0x3f7b0000,0x3f6d0000,0xbe483f80},{0x3ec43f35,0xbf55bec4,0xbec4bf35,0x3f0ebf6d},
{0x3ec4bf80,0x3f0e3f35,0xbec43f80,0xbf553f35},{0xbf6d3f35,0xbe48bf6d,0x3f6dbf35,0x3f7bbec4},
{0xbf6d0000,0x3f550000,0x3f6d0000,0x3f0e3f80},{0x3ec4bf35,0x3e483f6d,0xbec43f35,0xbf7bbec4},
{0x3ec43f80,0xbf7bbf35,0xbec4bf80,0x3e48bf35},{0xbf6dbf35,0x3f0ebec4,0x3f6d3f35,0x3f553f6d},
{0xbec40000,0x3e480000,0x3ec40000,0x3f7b3f80},{0xbf6dbf35,0x3f0e3ec4,0x3f6d3f35,0x3f553f6d},
{0xbf6dbf80,0x3f553f35,0x3f6d3f80,0x3f0e3f35},{0xbec4bf35,0x3f7b3f6d,0x3ec43f35,0x3e483ec4},
{0x3e3504f3,0x0,0x3e3504f3,0x0},{0x3e3504f3,0x0,0x3e3504f3,0x0},
{0x3e3504f3,0x0,0x3e3504f3,0x0},{0x3e3504f3,0x0,0x3e3504f3,0x0},
{0x3e3504f3,0x0,0x3e34cd21,0x3c0e1d7b},{0x3e3425ce,0x3c8df1a9,0x3e330f61,0x3cd47d09},
{0x3e318a86,0x3d0d42af,0x3e2f982b,0x3d2fefbb},{0x3e2d3986,0x3d523045,0x3e2a700c,0x3d73ef2f},
{0x3e3504f3,0x0,0x3e3425ce,0x3c8df1a9},{0x3e318a86,0x3d0d42af,0x3e2d3986,0x3d523045},
{0x3e273d75,0x3d8a8bd4,0x3e1fa512,0x3daaa9f2},{0x3e168317,0x3dc9234e,0x3e0bee0a,0x3de5acc6},
{0x3e3504f3,0x0,0x3e330f61,0x3cd47d09},{0x3e2d3986,0x3d523045,0x3e23a3b9,0x3d9aca9e},
{0x3e168317,0x3dc9234e,0x3e062061,0x3df3215c},{0x3de5acc6,0x3e0bee0a,0x3dba2005,0x3e1b43f5},
{0x3e3504f3,0x0,0x3e318a86,0x3d0d42af},{0x3e273d75,0x3d8a8bd4,0x3e168317,0x3dc9234e},
{0x3e000000,0x3e000000,0x3dc9234e,0x3e168317},{0x3d8a8bd4,0x3e273d75,0x3d0d42af,0x3e318a86},
{0x3e3504f3,0x0,0x3e2f982b,0x3d2fefbb},{0x3e1fa512,0x3daaa9f2,0x3e062061,0x3df3215c},
{0x3dc9234e,0x3e168317,0x3d73ef2f,0x3e2a700c},{0x3c8df1a9,0x3e3425ce,0xbcd47d09,0x3e330f61},
{0x3e3504f3,0x0,0x3e2d3986,0x3d523045},{0x3e168317,0x3dc9234e,0x3de5acc6,0x3e0bee0a},
{0x3d8a8bd4,0x3e273d75,0x3c8df1a9,0x3e3425ce},{0xbd0d42af,0x3e318a86,0xbdaaa9f2,0x3e1fa512},
{0x3e3504f3,0x0,0x3e2a700c,0x3d73ef2f},{0x3e0bee0a,0x3de5acc6,0x3dba2005,0x3e1b43f5},
{0x3d0d42af,0x3e318a86,0xbcd47d09,0x3e330f61},{0xbdaaa9f2,0x3e1fa512,0xbe062061,0x3df3215c},
{0x3e3504f3,0x0,0x3e350176,0x3b0e2b2f},{0x3e34f6fe,0x3b8e2871,0x3e34e58c,0x3bd535d0},
{0x3e34cd21,0x3c0e1d7b,0x3e34adbe,0x3c319a94},{0x3e348763,0x3c5510d4,0x3e345a13,0x3c787edd},
{0x3e3504f3,0x0,0x3e34adbe,0x3c319a94},{0x3e33a872,0x3cb14504,0x3e31f60b,0x3d0488f8},
{0x3e2f982b,0x3d2fefbb,0x3e2c911c,0x3d5aacf8},{0x3e28e3c6,0x3d824bc1,0x3e2493b5,0x3d96c37c},
{0x3e3504f3,0x0,0x3e33ea98,0x3c9f9e6a},{0x3e309ef7,0x3d1ea570,0x3e2b2c57,0x3d6b8cc0},
{0x3e23a3b9,0x3d9aca9e,0x3e1a1c9c,0x3dbdebf8},{0x3e0eb4b9,0x3ddebcd5,0x3e018fa5,0x3dfcd6d6},
{0x3e3504f3,0x0,0x3e32b87c,0x3ce60d19},{0x3e2be20a,0x3d63213d,0x3e20ae10,0x3da6bb9a},
{0x3e116566,0x3dd7aa8b,0x3dfcd6d6,0x3e018fa5},{0x3dd076ff,0x3e13ffa8,0x3d9ecbc9,0x3e22ad6e},
{0x3e3504f3,0x0,0x3e311828,0x3d15f6f4},{0x3e257d59,0x3d92b689,0x3e12b55b,0x3dd414dc},
{0x3df3215c,0x3e062061,0x3db64ce5,0x3e1c6553},{0x3d63213d,0x3e2be20a,0x3c9f9e6a,0x3e33ea98},
{0x3e3504f3,0x0,0x3e2f0a9c,0x3d388ade},{0x3e1d80a8,0x3db272be,0x3e018fa5,0x3dfcd6d6},
{0x3dba2005,0x3e1b43f5,0x3d49ab78,0x3e2ddb43},{0x3b8e2871,0x3e34f6fe,0xbd274dcf,0x3e301ef6},
{0x3e3504f3,0x0,0x3e2c911c,0x3d5aacf8},{0x3e13ffa8,0x3dd076ff,0x3ddb37ea,0x3e100fd7},
{0x3d73ef2f,0x3e2a700c,0x3bd535d0,0x3e34e58c},{0xbd411ee4,0x3e2e764c,0xbdc56dc2,0x3e17bc21},
{0x3e3504f3,0x0,0x3e29ad2e,0x3d7c4836},{0x3e0911c7,0x3dec794d,0x3dae91b5,0x3e1e95ec},
{0x3cd47d09,0x3e330f61,0xbd15f6f4,0x3e311828},{0xbdc1b099,0x3e18ef51,0xbe100fd7,0x3ddb37ea},
{0x3e3504f3,0x0,0x3e3504f3,0x0},{0x3e3504f3,0x0,0x3e3504f3,0x0},
{0x3e3504f3,0x0,0x3e3504f3,0x0},{0x3e3504f3,0x0,0x3e3504f3,0x0},
{0x3e273d75,0x3d8a8bd4,0x3e23a3b9,0x3d9aca9e},{0x3e1fa512,0x3daaa9f2,0x3e1b43f5,0x3dba2005},
{0x3e168317,0x3dc9234e,0x3e116566,0x3dd7aa8b},{0x3e0bee0a,0x3de5acc6,0x3e062061,0x3df3215c},
{0x3e000000,0x3e000000,0x3de5acc6,0x3e0bee0a},{0x3dc9234e,0x3e168317,0x3daaa9f2,0x3e1fa512},
{0x3d8a8bd4,0x3e273d75,0x3d523045,0x3e2d3986},{0x3d0d42af,0x3e318a86,0x3c8df1a9,0x3e3425ce},
{0x3d8a8bd4,0x3e273d75,0x3d2fefbb,0x3e2f982b},{0x3c8df1a9,0x3e3425ce,0xbc0e1d7b,0x3e34cd21},
{0xbd0d42af,0x3e318a86,0xbd73ef2f,0x3e2a700c},{0xbdaaa9f2,0x3e1fa512,0xbdd7aa8b,0x3e116566},
{0x0,0x3e3504f3,0xbd0d42af,0x3e318a86},{0xbd8a8bd4,0x3e273d75,0xbdc9234e,0x3e168317},
{0xbe000000,0x3e000000,0xbe168317,0x3dc9234e},{0xbe273d75,0x3d8a8bd4,0xbe318a86,0x3d0d42af},
{0xbd8a8bd4,0x3e273d75,0xbdd7aa8b,0x3e116566},{0xbe0bee0a,0x3de5acc6,0xbe23a3b9,0x3d9aca9e},
{0xbe318a86,0x3d0d42af,0xbe34cd21,0xbc0e1d7b},{0xbe2d3986,0xbd523045,0xbe1b43f5,0xbdba2005},
{0xbe000000,0x3e000000,0xbe1fa512,0x3daaa9f2},{0xbe318a86,0x3d0d42af,0xbe3425ce,0xbc8df1a9},
{0xbe273d75,0xbd8a8bd4,0xbe0bee0a,0xbde5acc6},{0xbdc9234e,0xbe168317,0xbd523045,0xbe2d3986},
{0xbe273d75,0x3d8a8bd4,0xbe34cd21,0x3c0e1d7b},{0xbe2d3986,0xbd523045,0xbe116566,0xbdd7aa8b},
{0xbdc9234e,0xbe168317,0xbd2fefbb,0xbe2f982b},{0x3c8df1a9,0xbe3425ce,0x3d9aca9e,0xbe23a3b9},
{0x3e3425ce,0x3c8df1a9,0x3e33ea98,0x3c9f9e6a},{0x3e33a872,0x3cb14504,0x3e335f5f,0x3cc2e4c8},
{0x3e330f61,0x3cd47d09,0x3e32b87c,0x3ce60d19},{0x3e325ab4,0x3cf7944a,0x3e31f60b,0x3d0488f8},
{0x3e1fa512,0x3daaa9f2,0x3e1a1c9c,0x3dbdebf8},{0x3e13ffa8,0x3dd076ff,0x3e0d541b,0x3de2392a},
{0x3e062061,0x3df3215c,0x3dfcd6d6,0x3e018fa5},{0x3dec794d,0x3e0911c7,0x3ddb37ea,0x3e100fd7},
{0x3de5acc6,0x3e0bee0a,0x3dc56dc2,0x3e17bc21},{0x3da2c6d5,0x3e21b0dd,0x3d7c4836,0x3e29ad2e},
{0x3d2fefbb,0x3e2f982b,0x3cc2e4c8,0x3e335f5f},{0x3b8e2871,0x3e34f6fe,0xbc787edd,0x3e345a13},
{0x3d523045,0x3e2d3986,0x3cc2e4c8,0x3e335f5f},{0xbb8e2871,0x3e34f6fe,0xbd0488f8,0x3e31f60b},
{0xbd73ef2f,0x3e2a700c,0xbdae91b5,0x3e1e95ec},{0xbddebcd5,0x3e0eb4b9,0xbe049fe5,0x3df66765},
{0xbc8df1a9,0x3e3425ce,0xbd5aacf8,0x3e2c911c},{0xbdb272be,0x3e1d80a8,0xbdefd1f4,0x3e079bb1},
{0xbe116566,0x3dd7aa8b,0xbe2493b5,0x3d96c37c},{0xbe309ef7,0x3d1ea570,0xbe350176,0x3b0e2b2f},
{0xbdaaa9f2,0x3e1fa512,0xbdf66765,0x3e049fe5},{0xbe18ef51,0x3dc1b099,0xbe2c911c,0x3d5aacf8},
{0xbe34cd21,0x3c0e1d7b,0xbe311828,0xbd15f6f4},{0xbe21b0dd,0xbda2c6d5,0xbe079bb1,0xbdefd1f4},
{0xbe0bee0a,0x3de5acc6,0xbe2813db,0x3d866e62},{0xbe348763,0x3c5510d4,0xbe301ef6,0xbd274dcf},
{0xbe1b43f5,0xbdba2005,0xbdefd1f4,0xbe079bb1},{0xbd92b689,0xbe257d59,0xbc9f9e6a,0xbe33ea98},
{0xbe2d3986,0x3d523045,0xbe34adbe,0xbc319a94},{0xbe257d59,0xbd92b689,0xbe018fa5,0xbdfcd6d6},
{0xbd9aca9e,0xbe23a3b9,0xbc787edd,0xbe345a13},{0x3d411ee4,0xbe2e764c,0x3dd414dc,0xbe12b55b},
{0x3e3504f3,0x0,0x3e34f6fe,0x3b8e2871},{0x3e34cd21,0x3c0e1d7b,0x3e348763,0x3c5510d4},
{0x3e3425ce,0x3c8df1a9,0x3e33a872,0x3cb14504},{0x3e330f61,0x3cd47d09,0x3e325ab4,0x3cf7944a},
{0x3e3504f3,0x0,0x3e348763,0x3c5510d4},{0x3e330f61,0x3cd47d09,0x3e309ef7,0x3d1ea570},
{0x3e2d3986,0x3d523045,0x3e28e3c6,0x3d824bc1},{0x3e23a3b9,0x3d9aca9e,0x3e1d80a8,0x3db272be},
{0x3e3504f3,0x0,0x3e33a872,0x3cb14504},{0x3e2f982b,0x3d2fefbb,0x3e28e3c6,0x3d824bc1},
{0x3e1fa512,0x3daaa9f2,0x3e13ffa8,0x3dd076ff},{0x3e062061,0x3df3215c,0x3dec794d,0x3e0911c7},
{0x3e3504f3,0x0,0x3e325ab4,0x3cf7944a},{0x3e2a700c,0x3d73ef2f,0x3e1d80a8,0x3db272be},
{0x3e0bee0a,0x3de5acc6,0x3dec794d,0x3e0911c7},{0x3dba2005,0x3e1b43f5,0x3d824bc1,0x3e28e3c6},
{0x3e3504f3,0x0,0x3e309ef7,0x3d1ea570},{0x3e23a3b9,0x3d9aca9e,0x3e0eb4b9,0x3ddebcd5},
{0x3de5acc6,0x3e0bee0a,0x3da2c6d5,0x3e21b0dd},{0x3d2fefbb,0x3e2f982b,0x3b8e2871,0x3e34f6fe},
{0x3e3504f3,0x0,0x3e2e764c,0x3d411ee4},{0x3e1b43f5,0x3dba2005,0x3df9a3ee,0x3e031a4c},
{0x3daaa9f2,0x3e1fa512,0x3d1ea570,0x3e309ef7},{0xbc0e1d7b,0x3e34cd21,0xbd63213d,0x3e2be20a},
{0x3e3504f3,0x0,0x3e2be20a,0x3d63213d},{0x3e116566,0x3dd7aa8b,0x3dd076ff,0x3e13ffa8},
{0x3d523045,0x3e2d3986,0xbb8e2871,0x3e34f6fe},{0xbd73ef2f,0x3e2a700c,0xbddebcd5,0x3e0eb4b9},
{0x3e3504f3,0x0,0x3e28e3c6,0x3d824bc1},{0x3e062061,0x3df3215c,0x3da2c6d5,0x3e21b0dd},
{0x3c8df1a9,0x3e3425ce,0xbd411ee4,0x3e2e764c},{0xbdd7aa8b,0x3e116566,0xbe18ef51,0x3dc1b099},
{0x3e3504f3,0x0,0x3e34e58c,0x3bd535d0},{0x3e348763,0x3c5510d4,0x3e33ea98,0x3c9f9e6a},
{0x3e330f61,0x3cd47d09,0x3e31f60b,0x3d0488f8},{0x3e309ef7,0x3d1ea570,0x3e2f0a9c,0x3d388ade},
{0x3e3504f3,0x0,0x3e345a13,0x3c787edd},{0x3e325ab4,0x3cf7944a,0x3e2f0a9c,0x3d388ade},
{0x3e2a700c,0x3d73ef2f,0x3e2493b5,0x3d96c37c},{0x3e1d80a8,0x3db272be,0x3e154440,0x3dccd119},
{0x3e3504f3,0x0,0x3e335f5f,0x3cc2e4c8},{0x3e2e764c,0x3d411ee4,0x3e26609c,0x3d8ea3ee},
{0x3e1b43f5,0x3dba2005,0x3e0d541b,0x3de2392a},{0x3df9a3ee,0x3e031a4c,0x3dd414dc,0x3e12b55b},
{0x3e3504f3,0x0,0x3e31f60b,0x3d0488f8},{0x3e28e3c6,0x3d824bc1,0x3e1a1c9c,0x3dbdebf8},
{0x3e062061,0x3df3215c,0x3ddb37ea,0x3e100fd7},{0x3da2c6d5,0x3e21b0dd,0x3d49ab78,0x3e2ddb43},
{0x3e3504f3,0x0,0x3e301ef6,0x3d274dcf},{0x3e21b0dd,0x3da2c6d5,0x3e0a8294,0x3de91788},
{0x3dd7aa8b,0x3e116566,0x3d8ea3ee,0x3e26609c},{0x3cf7944a,0x3e325ab4,0xbc319a94,0x3e34adbe},
{0x3e3504f3,0x0,0x3e2ddb43,0x3d49ab78},{0x3e18ef51,0x3dc1b099,0x3defd1f4,0x3e079bb1},
{0x3d9aca9e,0x3e23a3b9,0x3ce60d19,0x3e32b87c},{0xbcb14504,0x3e33a872,0xbd8ea3ee,0x3e26609c},
{0x3e3504f3,0x0,0x3e2b2c57,0x3d6b8cc0},{0x3e0eb4b9,0x3ddebcd5,0x3dc56dc2,0x3e17bc21},
{0x3d2fefbb,0x3e2f982b,0xbc787edd,0x3e345a13},{0xbd92b689,0x3e257d59,0xbdf66765,0x3e049fe5},
{0x3e3504f3,0x0,0x3e2813db,0x3d866e62},{0x3e031a4c,0x3df9a3ee,0x3d96c37c,0x3e2493b5},
{0x3c0e1d7b,0x3e34cd21,0xbd6b8cc0,0x3e2b2c57},{0xbdec794d,0x3e0911c7,0xbe20ae10,0x3da6bb9a},
{0x3e318a86,0x3d0d42af,0x3e309ef7,0x3d1ea570},{0x3e2f982b,0x3d2fefbb,0x3e2e764c,0x3d411ee4},
{0x3e2d3986,0x3d523045,0x3e2be20a,0x3d63213d},{0x3e2a700c,0x3d73ef2f,0x3e28e3c6,0x3d824bc1},
{0x3e168317,0x3dc9234e,0x3e0eb4b9,0x3ddebcd5},{0x3e062061,0x3df3215c,0x3df9a3ee,0x3e031a4c},
{0x3de5acc6,0x3e0bee0a,0x3dd076ff,0x3e13ffa8},{0x3dba2005,0x3e1b43f5,0x3da2c6d5,0x3e21b0dd},
{0x3dc9234e,0x3e168317,0x3da2c6d5,0x3e21b0dd},{0x3d73ef2f,0x3e2a700c,0x3d1ea570,0x3e309ef7},
{0x3c8df1a9,0x3e3425ce,0xbb8e2871,0x3e34f6fe},{0xbcd47d09,0x3e330f61,0xbd411ee4,0x3e2e764c},
{0x3d0d42af,0x3e318a86,0x3b8e2871,0x3e34f6fe},{0xbcd47d09,0x3e330f61,0xbd63213d,0x3e2be20a},
{0xbdaaa9f2,0x3e1fa512,0xbddebcd5,0x3e0eb4b9},{0xbe062061,0x3df3215c,0xbe18ef51,0x3dc1b099},
{0xbd0d42af,0x3e318a86,0xbd92b689,0x3e257d59},{0xbdd7aa8b,0x3e116566,0xbe0911c7,0x3dec794d},
{0xbe1fa512,0x3daaa9f2,0xbe2e764c,0x3d411ee4},{0xbe34cd21,0x3c0e1d7b,0xbe325ab4,0xbcf7944a},
{0xbdc9234e,0x3e168317,0xbe0911c7,0x3dec794d},{0xbe23a3b9,0x3d9aca9e,0xbe325ab4,0x3cf7944a},
{0xbe3425ce,0xbc8df1a9,0xbe28e3c6,0xbd824bc1},{0xbe116566,0xbdd7aa8b,0xbddebcd5,0xbe0eb4b9},
{0xbe168317,0x3dc9234e,0xbe2e764c,0x3d411ee4},{0xbe34cd21,0xbc0e1d7b,0xbe28e3c6,0xbd824bc1},
{0xbe0bee0a,0xbde5acc6,0xbdc1b099,0xbe18ef51},{0xbd2fefbb,0xbe2f982b,0x3c5510d4,0xbe348763},
{0xbe318a86,0x3d0d42af,0xbe325ab4,0xbcf7944a},{0xbe1b43f5,0xbdba2005,0xbddebcd5,0xbe0eb4b9},
{0xbd523045,0xbe2d3986,0x3c5510d4,0xbe348763},{0x3d9aca9e,0xbe23a3b9,0x3e031a4c,0xbdf9a3ee},
{0x3e2d3986,0x3d523045,0x3e2b2c57,0x3d6b8cc0},{0x3e28e3c6,0x3d824bc1,0x3e26609c,0x3d8ea3ee},
{0x3e23a3b9,0x3d9aca9e,0x3e20ae10,0x3da6bb9a},{0x3e1d80a8,0x3db272be,0x3e1a1c9c,0x3dbdebf8},
{0x3e0bee0a,0x3de5acc6,0x3e018fa5,0x3dfcd6d6},{0x3dec794d,0x3e0911c7,0x3dd414dc,0x3e12b55b},
{0x3dba2005,0x3e1b43f5,0x3d9ecbc9,0x3e22ad6e},{0x3d824bc1,0x3e28e3c6,0x3d49ab78,0x3e2ddb43},
{0x3daaa9f2,0x3e1fa512,0x3d7c4836,0x3e29ad2e},{0x3d1ea570,0x3e309ef7,0x3c787edd,0x3e345a13},
{0xbc0e1d7b,0x3e34cd21,0xbd0488f8,0x3e31f60b},{0xbd63213d,0x3e2be20a,0xbd9ecbc9,0x3e22ad6e},
{0x3c8df1a9,0x3e3425ce,0xbc787edd,0x3e345a13},{0xbd411ee4,0x3e2e764c,0xbd9ecbc9,0x3e22ad6e},
{0xbdd7aa8b,0x3e116566,0xbe049fe5,0x3df66765},{0xbe18ef51,0x3dc1b099,0xbe2813db,0x3d866e62},
{0xbd523045,0x3e2d3986,0xbdb64ce5,0x3e1c6553},{0xbdf9a3ee,0x3e031a4c,0xbe17bc21,0x3dc56dc2},
{0xbe2a700c,0x3d73ef2f,0xbe33ea98,0x3c9f9e6a},{0xbe33a872,0xbcb14504,0xbe29ad2e,0xbd7c4836},
{0xbde5acc6,0x3e0bee0a,0xbe154440,0x3dccd119},{0xbe2be20a,0x3d63213d,0xbe34e58c,0x3bd535d0},
{0xbe2f982b,0xbd2fefbb,0xbe1c6553,0xbdb64ce5},{0xbdf9a3ee,0xbe031a4c,0xbda6bb9a,0xbe20ae10},
{0xbe1fa512,0x3daaa9f2,0xbe32b87c,0x3ce60d19},{0xbe325ab4,0xbcf7944a,0xbe1e95ec,0xbdae91b5},
{0xbdf3215c,0xbe062061,0xbd8ea3ee,0xbe26609c},{0xbc5510d4,0xbe348763,0x3d388ade,0xbe2f0a9c},
{0xbe3425ce,0x3c8df1a9,0xbe2ddb43,0xbd49ab78},{0xbe0eb4b9,0xbddebcd5,0xbdb64ce5,0xbe1c6553},
{0xbcd47d09,0xbe330f61,0x3d274dcf,0xbe301ef6},{0x3dd076ff,0xbe13ffa8,0x3e17bc21,0xbdc56dc2},
};

__device__ uint4 g_G1[16 * 8 * 128 * 8];
__device__ uint4 g_G2[128 * 16 * 8 * 8];
__device__ uint32_t g_G1x[128 * 16];
__device__ uint32_t g_G2x[16 * 128];
__device__ uint4 g_A[16 * 16 * 128 * 4];
__device__ uint4 g_W[128 * 384];
__device__ unsigned g_ctl[4 * 32];

#define TRAP(code) __trap()
__device__ __forceinline__ uint32_t smem_u32(const void* p) { return (uint32_t)__cvta_generic_to_shared(p); }
__device__ __forceinline__ long long clk64() { long long t; asm volatile("mov.u64 %0, %%clock64;" : "=l"(t)::"memory"); return t; }
constexpr long long TIMEOUT_CLK = 400000000ll;
__device__ __forceinline__ void mbar_init(uint32_t bar, int cnt) { asm volatile("mbarrier.init.shared::cta.b64 [%0], %1;" ::"r"(bar), "r"(cnt) : "memory"); }
__device__ __forceinline__ void mbar_expect(uint32_t bar, uint32_t bytes) { asm volatile("mbarrier.arrive.expect_tx.shared::cta.b64 _, [%0], %1;" ::"r"(bar), "r"(bytes) : "memory"); }
__device__ __forceinline__ void mbar_arrive(uint32_t bar) { asm volatile("mbarrier.arrive.shared::cta.b64 _, [%0];" ::"r"(bar) : "memory"); }
__device__ __forceinline__ bool mbar_try(uint32_t bar, uint32_t parity) {
  uint32_t ok;
  asm volatile("{\n.reg .pred p;\nmbarrier.try_wait.parity.shared::cta.b64 p, [%1], %2;\nselp.u32 %0, 1, 0, p;\n}" : "=r"(ok) : "r"(bar), "r"(parity) : "memory");
  return ok;
}
__device__ __forceinline__ bool mbar_try_cluster(uint32_t bar, uint32_t parity) {
  uint32_t ok;
  asm volatile("{\n.reg .pred p;\nmbarrier.try_wait.parity.acquire.cluster.shared::cta.b64 p, [%1], %2;\nselp.u32 %0, 1, 0, p;\n}" : "=r"(ok) : "r"(bar), "r"(parity) : "memory");
  return ok;
}
constexpr int SPIN_CAP = 1 << 22;
__device__ __forceinline__ void mbar_wait(uint32_t bar, uint32_t parity) {
  int n = 0;
#pragma unroll 1
  while (!mbar_try(bar, parity)) if (++n > SPIN_CAP) TRAP(16 + (((bar - 1024 - OFF_BAR) >> 3) & 31));
}
__device__ __forceinline__ void mbar_wait_cluster(uint32_t bar, uint32_t parity) {
  int n = 0;
#pragma unroll 1
  while (!mbar_try_cluster(bar, parity)) if (++n > SPIN_CAP) TRAP(16 + (((bar - 1024 - OFF_BAR) >> 3) & 31));
}
__device__ __forceinline__ void bar_sync(int id, int n) { asm volatile("bar.sync %0, %1;" ::"r"(id), "r"(n) : "memory"); }
__device__ __forceinline__ void bar_arrive(int id, int n) { asm volatile("bar.arrive %0, %1;" ::"r"(id), "r"(n) : "memory"); }
__device__ __forceinline__ uint32_t mapa(uint32_t a, uint32_t r) { uint32_t o; asm("mapa.shared::cluster.u32 %0, %1, %2;" : "=r"(o) : "r"(a), "r"(r)); return o; }
__device__ __forceinline__ void bulk_g2s(uint32_t dst, const void* src, uint32_t bytes, uint32_t bar) {
  asm volatile("cp.async.bulk.shared::cluster.global.mbarrier::complete_tx::bytes [%0], [%1], %2, [%3];" ::"r"(dst), "l"(src), "r"(bytes), "r"(bar) : "memory");
}
__device__ __forceinline__ void bulk_s2g(void* dst, uint32_t src, uint32_t bytes) {
  asm volatile("cp.async.bulk.global.shared::cta.bulk_group [%0], [%1], %2;" ::"l"(dst), "r"(src), "r"(bytes) : "memory");
}
__device__ __forceinline__ void tma2d(uint32_t dst, const CUtensorMap* m, int c0, int c1, uint32_t bar) {
  asm volatile("cp.async.bulk.tensor.2d.shared::cluster.global.mbarrier::complete_tx::bytes [%0], [%1, {%3, %4}], [%2];" ::"r"(dst), "l"(m), "r"(bar), "r"(c0), "r"(c1) : "memory");
}
__device__ __forceinline__ void tma3d(uint32_t dst, const CUtensorMap* m, int c0, int c1, int c2, uint32_t bar) {
  asm volatile("cp.async.bulk.tensor.3d.shared::cluster.global.mbarrier::complete_tx::bytes [%0], [%1, {%3, %4, %5}], [%2];" ::"r"(dst), "l"(m), "r"(bar), "r"(c0), "r"(c1), "r"(c2) : "memory");
}
__device__ __forceinline__ void tma3d_red_add(const CUtensorMap* m, int c0, int c1, int c2, uint32_t src) {
  asm volatile("cp.reduce.async.bulk.tensor.3d.global.shared::cta.add.tile.bulk_group [%0, {%2, %3, %4}], [%1];" ::"l"(m), "r"(src), "r"(c0), "r"(c1), "r"(c2) : "memory");
}
__device__ __forceinline__ void bulk_commit() { asm volatile("cp.async.bulk.commit_group;" ::: "memory"); }
__device__ __forceinline__ void bulk_wait_all() { asm volatile("cp.async.bulk.wait_group 0;" ::: "memory"); }
__device__ __forceinline__ void bulk_wait_read() { asm volatile("cp.async.bulk.wait_group.read 0;" ::: "memory"); }
__device__ __forceinline__ void l2_prefetch(const void* p, uint32_t bytes) { asm volatile("cp.async.bulk.prefetch.L2.global [%0], %1;" ::"l"(p), "r"(bytes) : "memory"); }
__device__ __forceinline__ void fence_async_smem() { asm volatile("fence.proxy.async.shared::cta;" ::: "memory"); }
__device__ __forceinline__ void fence_async_global() { asm volatile("fence.proxy.async.global;" ::: "memory"); }
__device__ __forceinline__ void fence_release_gpu() { asm volatile("fence.release.gpu;" ::: "memory"); }
__device__ __forceinline__ uint4 lds128(uint32_t a) { uint4 v; asm volatile("ld.shared.v4.u32 {%0,%1,%2,%3}, [%4];" : "=r"(v.x), "=r"(v.y), "=r"(v.z), "=r"(v.w) : "r"(a) : "memory"); return v; }
__device__ __forceinline__ uint32_t lds32(uint32_t a) { uint32_t v; asm volatile("ld.shared.u32 %0, [%1];" : "=r"(v) : "r"(a) : "memory"); return v; }
__device__ __forceinline__ void sts128(uint32_t a, uint4 v) { asm volatile("st.shared.v4.u32 [%0], {%1,%2,%3,%4};" ::"r"(a), "r"(v.x), "r"(v.y), "r"(v.z), "r"(v.w) : "memory"); }
__device__ __forceinline__ void sts32(uint32_t a, uint32_t v) { asm volatile("st.shared.u32 [%0], %1;" ::"r"(a), "r"(v) : "memory"); }
__device__ __forceinline__ uint4 ldg_relaxed128(const void* p) {
  unsigned long long a, b;
  asm volatile("ld.relaxed.gpu.global.v2.b64 {%0,%1}, [%2];" : "=l"(a), "=l"(b) : "l"(p) : "memory");
  return make_uint4((uint32_t)a, (uint32_t)(a >> 32), (uint32_t)b, (uint32_t)(b >> 32));
}
__device__ __forceinline__ uint32_t ldg_relaxed32(const void* p) { uint32_t v; asm volatile("ld.relaxed.gpu.global.u32 %0, [%1];" : "=r"(v) : "l"(p) : "memory"); return v; }
__device__ __forceinline__ uint32_t ldg_acquire32(const void* p) { uint32_t v; asm volatile("ld.acquire.gpu.global.u32 %0, [%1];" : "=r"(v) : "l"(p) : "memory"); return v; }
__device__ __forceinline__ void stg_relaxed128(void* p, uint4 v) {
  asm volatile("st.relaxed.gpu.global.v2.b64 [%0], {%1,%2};" ::"l"(p), "l"((unsigned long long)v.x | ((unsigned long long)v.y << 32)), "l"((unsigned long long)v.z | ((unsigned long long)v.w << 32)) : "memory");
}
__device__ __forceinline__ void stg_relaxed32(void* p, uint32_t v) { asm volatile("st.relaxed.gpu.global.u32 [%0], %1;" ::"l"(p), "r"(v) : "memory"); }
__device__ __forceinline__ void red_add(unsigned* p) { asm volatile("red.relaxed.gpu.global.add.u32 [%0], 1;" ::"l"(p) : "memory"); }
__device__ __forceinline__ uint2 ldg_nc64(const void* p) { uint2 v; asm volatile("ld.global.nc.L1::no_allocate.v2.u32 {%0,%1}, [%2];" : "=r"(v.x), "=r"(v.y) : "l"(p)); return v; }
__device__ __forceinline__ uint2 ldg_nc64_if(const void* p, int pred) {
  uint2 v;
  asm volatile("{\n.reg .pred p;\nsetp.ne.b32 p, %3, 0;\nmov.b32 %0, 0;\nmov.b32 %1, 0;\n@p ld.global.nc.L1::no_allocate.v2.u32 {%0,%1}, [%2];\n}" : "=&r"(v.x), "=&r"(v.y) : "l"(p), "r"(pred));
  return v;
}
__device__ __forceinline__ uint4 ldg_nc128(const void* p) { uint4 v; asm volatile("ld.global.nc.L1::no_allocate.v4.u32 {%0,%1,%2,%3}, [%4];" : "=r"(v.x), "=r"(v.y), "=r"(v.z), "=r"(v.w) : "l"(p)); return v; }
__device__ __forceinline__ uint32_t ldg_nc16(const void* p) { uint32_t v; asm volatile("ld.global.nc.u16 %0, [%1];" : "=r"(v) : "l"(p)); return v; }
__device__ __forceinline__ uint32_t pack_h(float lo, float hi) { uint32_t r; asm("cvt.rn.f16x2.f32 %0, %1, %2;" : "=r"(r) : "f"(hi), "f"(lo)); return r; }
__device__ __forceinline__ uint32_t pack_b(float lo, float hi) { uint32_t r; asm("cvt.rn.bf16x2.f32 %0, %1, %2;" : "=r"(r) : "f"(hi), "f"(lo)); return r; }
__device__ __forceinline__ float blo(uint32_t w) { return __uint_as_float(w << 16); }
__device__ __forceinline__ float bhi(uint32_t w) { return __uint_as_float(w & 0xffff0000u); }
__device__ __forceinline__ float fcos(float x) { float r; asm("cos.approx.f32 %0, %1;" : "=f"(r) : "f"(x)); return r; }
__device__ __forceinline__ float fsin(float x) { float r; asm("sin.approx.f32 %0, %1;" : "=f"(r) : "f"(x)); return r; }
__device__ __forceinline__ float ftanh(float x) { float r; asm("tanh.approx.f32 %0, %1;" : "=f"(r) : "f"(x)); return r; }
__device__ __forceinline__ float ang2048(int idx) { return (float)(((idx + 1024) & 2047) - 1024) * 3.0679615757712823e-3f; }
__device__ __forceinline__ void mma_h(float (&d)[4], uint32_t a0, uint32_t a1, uint32_t a2, uint32_t a3, uint32_t b0, uint32_t b1) {
  asm("mma.sync.aligned.m16n8k16.row.col.f32.f16.f16.f32 {%0,%1,%2,%3}, {%4,%5,%6,%7}, {%8,%9}, {%0,%1,%2,%3};"
      : "+f"(d[0]), "+f"(d[1]), "+f"(d[2]), "+f"(d[3]) : "r"(a0), "r"(a1), "r"(a2), "r"(a3), "r"(b0), "r"(b1));
}
__device__ __forceinline__ void mma_b(float (&d)[4], uint32_t a0, uint32_t a1, uint32_t a2, uint32_t a3, uint32_t b0, uint32_t b1) {
  asm("mma.sync.aligned.m16n8k16.row.col.f32.bf16.bf16.f32 {%0,%1,%2,%3}, {%4,%5,%6,%7}, {%8,%9}, {%0,%1,%2,%3};"
      : "+f"(d[0]), "+f"(d[1]), "+f"(d[2]), "+f"(d[3]) : "r"(a0), "r"(a1), "r"(a2), "r"(a3), "r"(b0), "r"(b1));
}
__device__ __forceinline__ void mma_h(float (&d)[4], const uint4& a, uint32_t b0, uint32_t b1) { mma_h(d, a.x, a.y, a.z, a.w, b0, b1); }
__device__ __forceinline__ void mma_b(float (&d)[4], const uint4& a, uint32_t b0, uint32_t b1) { mma_b(d, a.x, a.y, a.z, a.w, b0, b1); }
__device__ __forceinline__ void mma_h0(float (&d)[4], uint32_t a0, uint32_t a1, uint32_t a2, uint32_t a3, uint32_t b0, uint32_t b1) {
  asm("mma.sync.aligned.m16n8k16.row.col.f32.f16.f16.f32 {%0,%1,%2,%3}, {%4,%5,%6,%7}, {%8,%9}, {%10,%10,%10,%10};"
      : "=f"(d[0]), "=f"(d[1]), "=f"(d[2]), "=f"(d[3]) : "r"(a0), "r"(a1), "r"(a2), "r"(a3), "r"(b0), "r"(b1), "f"(0.f));
}
__device__ __forceinline__ void mma_b0(float (&d)[4], uint32_t a0, uint32_t a1, uint32_t a2, uint32_t a3, uint32_t b0, uint32_t b1) {
  asm("mma.sync.aligned.m16n8k16.row.col.f32.bf16.bf16.f32 {%0,%1,%2,%3}, {%4,%5,%6,%7}, {%8,%9}, {%10,%10,%10,%10};"
      : "=f"(d[0]), "=f"(d[1]), "=f"(d[2]), "=f"(d[3]) : "r"(a0), "r"(a1), "r"(a2), "r"(a3), "r"(b0), "r"(b1), "f"(0.f));
}
__device__ __forceinline__ void mma_h0(float (&d)[4], const uint4& a, uint32_t b0, uint32_t b1) { mma_h0(d, a.x, a.y, a.z, a.w, b0, b1); }
__device__ __forceinline__ void mma_b0(float (&d)[4], const uint4& a, uint32_t b0, uint32_t b1) { mma_b0(d, a.x, a.y, a.z, a.w, b0, b1); }
__device__ __forceinline__ uint32_t comp(const uint4& v, int c) { return c == 0 ? v.x : c == 1 ? v.y : c == 2 ? v.z : v.w; }
__device__ __forceinline__ uint32_t plo(uint32_t a, uint32_t b) { return __byte_perm(a, b, 0x5410); }
__device__ __forceinline__ uint32_t phi(uint32_t a, uint32_t b) { return __byte_perm(a, b, 0x7632); }
__device__ __forceinline__ uint32_t hmul2(uint32_t a, uint32_t b) { uint32_t r; asm("mul.rn.f16x2 %0, %1, %2;" : "=r"(r) : "r"(a), "r"(b)); return r; }
__device__ __forceinline__ uint32_t hfma2(uint32_t a, uint32_t b, uint32_t c) { uint32_t r; asm("fma.rn.f16x2 %0, %1, %2, %3;" : "=r"(r) : "r"(a), "r"(b), "r"(c)); return r; }
__device__ __forceinline__ uint32_t hneg2(uint32_t a) { uint32_t r; asm("neg.f16x2 %0, %1;" : "=r"(r) : "r"(a)); return r; }
__device__ __forceinline__ void twiddle_h2(uint32_t re, uint32_t im, uint32_t c, uint32_t s, uint32_t& ore, uint32_t& oim) {
  ore = hfma2(re, c, hmul2(im, s));
  oim = hfma2(im, c, hneg2(hmul2(re, s)));
}
__device__ __forceinline__ uint32_t tag(uint32_t w, uint32_t par) { return (w & ~1u) | par; }

template <int N> __device__ __forceinline__ void wgmma_ss_n256(float (&d)[N], uint64_t da, uint64_t db, int acc) {
  asm volatile("{\n.reg .pred p;\nsetp.ne.b32 p, %130, 0;\n"
    "wgmma.mma_async.sync.aligned.m64n256k16.f32.bf16.bf16 "
    "{%0,%1,%2,%3,%4,%5,%6,%7,%8,%9,%10,%11,%12,%13,%14,%15,"
    "%16,%17,%18,%19,%20,%21,%22,%23,%24,%25,%26,%27,%28,%29,%30,%31,"
    "%32,%33,%34,%35,%36,%37,%38,%39,%40,%41,%42,%43,%44,%45,%46,%47,"
    "%48,%49,%50,%51,%52,%53,%54,%55,%56,%57,%58,%59,%60,%61,%62,%63,"
    "%64,%65,%66,%67,%68,%69,%70,%71,%72,%73,%74,%75,%76,%77,%78,%79,"
    "%80,%81,%82,%83,%84,%85,%86,%87,%88,%89,%90,%91,%92,%93,%94,%95,"
    "%96,%97,%98,%99,%100,%101,%102,%103,%104,%105,%106,%107,%108,%109,%110,%111,"
    "%112,%113,%114,%115,%116,%117,%118,%119,%120,%121,%122,%123,%124,%125,%126,%127}, %128, %129, p, 1, 1, 0, 1;\n}\n"
    : "+f"(d[0]), "+f"(d[1]), "+f"(d[2]), "+f"(d[3]), "+f"(d[4]), "+f"(d[5]), "+f"(d[6]), "+f"(d[7]), "+f"(d[8]), "+f"(d[9]), "+f"(d[10]), "+f"(d[11]), "+f"(d[12]), "+f"(d[13]), "+f"(d[14]), "+f"(d[15]), "+f"(d[16]), "+f"(d[17]), "+f"(d[18]), "+f"(d[19]), "+f"(d[20]), "+f"(d[21]), "+f"(d[22]), "+f"(d[23]), "+f"(d[24]), "+f"(d[25]), "+f"(d[26]), "+f"(d[27]), "+f"(d[28]), "+f"(d[29]), "+f"(d[30]), "+f"(d[31]), "+f"(d[32]), "+f"(d[33]), "+f"(d[34]), "+f"(d[35]), "+f"(d[36]), "+f"(d[37]), "+f"(d[38]), "+f"(d[39]), "+f"(d[40]), "+f"(d[41]), "+f"(d[42]), "+f"(d[43]), "+f"(d[44]), "+f"(d[45]), "+f"(d[46]), "+f"(d[47]), "+f"(d[48]), "+f"(d[49]), "+f"(d[50]), "+f"(d[51]), "+f"(d[52]), "+f"(d[53]), "+f"(d[54]), "+f"(d[55]), "+f"(d[56]), "+f"(d[57]), "+f"(d[58]), "+f"(d[59]), "+f"(d[60]), "+f"(d[61]), "+f"(d[62]), "+f"(d[63]), "+f"(d[64]), "+f"(d[65]), "+f"(d[66]), "+f"(d[67]), "+f"(d[68]), "+f"(d[69]), "+f"(d[70]), "+f"(d[71]), "+f"(d[72]), "+f"(d[73]), "+f"(d[74]), "+f"(d[75]), "+f"(d[76]), "+f"(d[77]), "+f"(d[78]), "+f"(d[79]), "+f"(d[80]), "+f"(d[81]), "+f"(d[82]), "+f"(d[83]), "+f"(d[84]), "+f"(d[85]), "+f"(d[86]), "+f"(d[87]), "+f"(d[88]), "+f"(d[89]), "+f"(d[90]), "+f"(d[91]), "+f"(d[92]), "+f"(d[93]), "+f"(d[94]), "+f"(d[95]), "+f"(d[96]), "+f"(d[97]), "+f"(d[98]), "+f"(d[99]), "+f"(d[100]), "+f"(d[101]), "+f"(d[102]), "+f"(d[103]), "+f"(d[104]), "+f"(d[105]), "+f"(d[106]), "+f"(d[107]), "+f"(d[108]), "+f"(d[109]), "+f"(d[110]), "+f"(d[111]), "+f"(d[112]), "+f"(d[113]), "+f"(d[114]), "+f"(d[115]), "+f"(d[116]), "+f"(d[117]), "+f"(d[118]), "+f"(d[119]), "+f"(d[120]), "+f"(d[121]), "+f"(d[122]), "+f"(d[123]), "+f"(d[124]), "+f"(d[125]), "+f"(d[126]), "+f"(d[127])
    : "l"(da), "l"(db), "r"(acc));
}
template <int N> __device__ __forceinline__ void wgmma_ss_n96(float (&d)[N], uint64_t da, uint64_t db, int acc) {
  asm volatile("{\n.reg .pred p;\nsetp.ne.b32 p, %50, 0;\n"
    "wgmma.mma_async.sync.aligned.m64n96k16.f32.bf16.bf16 "
    "{%0,%1,%2,%3,%4,%5,%6,%7,%8,%9,%10,%11,%12,%13,%14,%15,"
    "%16,%17,%18,%19,%20,%21,%22,%23,%24,%25,%26,%27,%28,%29,%30,%31,"
    "%32,%33,%34,%35,%36,%37,%38,%39,%40,%41,%42,%43,%44,%45,%46,%47}, %48, %49, p, 1, 1, 0, 1;\n}\n"
    : "+f"(d[0]), "+f"(d[1]), "+f"(d[2]), "+f"(d[3]), "+f"(d[4]), "+f"(d[5]), "+f"(d[6]), "+f"(d[7]), "+f"(d[8]), "+f"(d[9]), "+f"(d[10]), "+f"(d[11]), "+f"(d[12]), "+f"(d[13]), "+f"(d[14]), "+f"(d[15]), "+f"(d[16]), "+f"(d[17]), "+f"(d[18]), "+f"(d[19]), "+f"(d[20]), "+f"(d[21]), "+f"(d[22]), "+f"(d[23]), "+f"(d[24]), "+f"(d[25]), "+f"(d[26]), "+f"(d[27]), "+f"(d[28]), "+f"(d[29]), "+f"(d[30]), "+f"(d[31]), "+f"(d[32]), "+f"(d[33]), "+f"(d[34]), "+f"(d[35]), "+f"(d[36]), "+f"(d[37]), "+f"(d[38]), "+f"(d[39]), "+f"(d[40]), "+f"(d[41]), "+f"(d[42]), "+f"(d[43]), "+f"(d[44]), "+f"(d[45]), "+f"(d[46]), "+f"(d[47])
    : "l"(da), "l"(db), "r"(acc));
}
template <int O, int N> __device__ __forceinline__ void wgmma_rs_n128(float (&d)[N], uint32_t a0, uint32_t a1, uint32_t a2, uint32_t a3, uint64_t db, int acc) {
  asm volatile("{\n.reg .pred p;\nsetp.ne.b32 p, %69, 0;\n"
    "wgmma.mma_async.sync.aligned.m64n128k16.f32.bf16.bf16 "
    "{%0,%1,%2,%3,%4,%5,%6,%7,%8,%9,%10,%11,%12,%13,%14,%15,"
    "%16,%17,%18,%19,%20,%21,%22,%23,%24,%25,%26,%27,%28,%29,%30,%31,"
    "%32,%33,%34,%35,%36,%37,%38,%39,%40,%41,%42,%43,%44,%45,%46,%47,"
    "%48,%49,%50,%51,%52,%53,%54,%55,%56,%57,%58,%59,%60,%61,%62,%63}, {%64,%65,%66,%67}, %68, p, 1, 1, 1;\n}\n"
    : "+f"(d[O + 0]), "+f"(d[O + 1]), "+f"(d[O + 2]), "+f"(d[O + 3]), "+f"(d[O + 4]), "+f"(d[O + 5]), "+f"(d[O + 6]), "+f"(d[O + 7]), "+f"(d[O + 8]), "+f"(d[O + 9]), "+f"(d[O + 10]), "+f"(d[O + 11]), "+f"(d[O + 12]), "+f"(d[O + 13]), "+f"(d[O + 14]), "+f"(d[O + 15]), "+f"(d[O + 16]), "+f"(d[O + 17]), "+f"(d[O + 18]), "+f"(d[O + 19]), "+f"(d[O + 20]), "+f"(d[O + 21]), "+f"(d[O + 22]), "+f"(d[O + 23]), "+f"(d[O + 24]), "+f"(d[O + 25]), "+f"(d[O + 26]), "+f"(d[O + 27]), "+f"(d[O + 28]), "+f"(d[O + 29]), "+f"(d[O + 30]), "+f"(d[O + 31]), "+f"(d[O + 32]), "+f"(d[O + 33]), "+f"(d[O + 34]), "+f"(d[O + 35]), "+f"(d[O + 36]), "+f"(d[O + 37]), "+f"(d[O + 38]), "+f"(d[O + 39]), "+f"(d[O + 40]), "+f"(d[O + 41]), "+f"(d[O + 42]), "+f"(d[O + 43]), "+f"(d[O + 44]), "+f"(d[O + 45]), "+f"(d[O + 46]), "+f"(d[O + 47]), "+f"(d[O + 48]), "+f"(d[O + 49]), "+f"(d[O + 50]), "+f"(d[O + 51]), "+f"(d[O + 52]), "+f"(d[O + 53]), "+f"(d[O + 54]), "+f"(d[O + 55]), "+f"(d[O + 56]), "+f"(d[O + 57]), "+f"(d[O + 58]), "+f"(d[O + 59]), "+f"(d[O + 60]), "+f"(d[O + 61]), "+f"(d[O + 62]), "+f"(d[O + 63])
    : "r"(a0), "r"(a1), "r"(a2), "r"(a3), "l"(db), "r"(acc));
}

__device__ __forceinline__ void wg_fence() { asm volatile("wgmma.fence.sync.aligned;" ::: "memory"); }
__device__ __forceinline__ void wg_commit() { asm volatile("wgmma.commit_group.sync.aligned;" ::: "memory"); }
template <int N> __device__ __forceinline__ void wg_wait() { asm volatile("wgmma.wait_group.sync.aligned %0;" ::"n"(N) : "memory"); }
template <int N> __device__ __forceinline__ void reg_fence(float (&d)[N]) {
#pragma unroll
  for (int i = 0; i < N; i++) asm volatile("" : "+f"(d[i])::"memory");
}
constexpr uint32_t SMEM_BASE = 1024;
__host__ __device__ constexpr uint64_t mkdesc(uint32_t off, uint32_t lbo, uint32_t sbo, uint32_t mode) {
  return (uint64_t)((SMEM_BASE + off) >> 4) | ((uint64_t)(lbo >> 4) << 16) | ((uint64_t)(sbo >> 4) << 32) | ((uint64_t)mode << 62);
}

template <int PH, class F>
__device__ __forceinline__ void load4_validated(uint4 (&v)[4], const uint4* src, uint32_t par, F filler) {
  const uint32_t want = par ? ~0u : 0u;
#pragma unroll
  for (int j = 0; j < 4; j++) v[j] = ldg_relaxed128(src + j * 256);
  filler();
  int n = 0;
#pragma unroll 1
  while (((v[0].x ^ want) | (v[0].z ^ want) | (v[1].x ^ want) | (v[1].z ^ want) | (v[2].x ^ want) | (v[2].z ^ want) | (v[3].x ^ want) | (v[3].z ^ want)) & 1u) {
    if (++n > SPIN_CAP) TRAP(1);
#pragma unroll
    for (int j = 0; j < 4; j++) v[j] = ldg_relaxed128(src + j * 256);
  }
}
__device__ __forceinline__ uint32_t reload32(const void* p, uint32_t par) {
#pragma unroll 1
  for (int n = 0;; n++) {
    const uint32_t v = ldg_relaxed32(p);
    if (((v ^ par) & 1u) == 0) return v;
    if (n > SPIN_CAP) TRAP(2);
  }
}
__device__ __forceinline__ void spin(int clks, uint32_t ad) {
  if (clks > 0) { const uint32_t d = lds32(ad) >> 8; long long t0; asm volatile("{\n.reg .u64 t;\nmov.u64 t, %%clock64;\ncvt.u64.u32 %0, %1;\nadd.u64 %0, %0, t;\n}" : "=l"(t0) : "r"(d) : "memory"); while (clk64() - t0 < clks) {} }
}
template <bool ACQ> __device__ __forceinline__ void poll_ge(const unsigned* p, unsigned target) {
#pragma unroll 1
  for (int n = 0;; n++) {
    const unsigned v = ACQ ? ldg_acquire32(p) : ldg_relaxed32(p);
    if ((int)(v - target) >= 0) return;
    if (n > SPIN_CAP) TRAP(ACQ ? 4 : 3);
  }
}

#define PROF(side, i)
#define PROFD(side, i, dep)

struct BTab { uint4 fc, fs, fn, tw, f8b, f8a, ti0, ti1, gc, gs, gn; };
__device__ __forceinline__ void phaseB_col(const BTab& T, uint32_t r0, uint32_t r1, uint32_t r2, uint32_t r3,
                                           const float (&fwr)[4], const float (&fwi)[4], uint32_t (&o)[4]) {
  const uint32_t br0 = plo(r0, r1), br1 = plo(r2, r3), bi0 = phi(r0, r1), bi1 = phi(r2, r3);
  float re[4], im[4];
  mma_h0(re, T.fc, br0, br1); mma_h0(im, T.fc, bi0, bi1);
  mma_h(re, T.fs, bi0, bi1); mma_h(im, T.fn, br0, br1);
  float a[4], b[4];
  uint32_t a0, a1, a2, a3;
  twiddle_h2(pack_h(re[0], re[1]), pack_h(im[0], im[1]), T.tw.x, T.tw.y, a0, a2);
  twiddle_h2(pack_h(re[2], re[3]), pack_h(im[2], im[3]), T.tw.z, T.tw.w, a1, a3);
  mma_h0(re, a0, a1, a2, a3, T.f8b.x, T.f8b.y);
  mma_h0(im, a0, a1, a2, a3, T.f8b.z, T.f8b.w);
#pragma unroll
  for (int e = 0; e < 4; e++) {
    const float wr = fwr[e], wi = fwi[e];
    a[e] = re[e] * wr - im[e] * wi;
    b[e] = re[e] * wi + im[e] * wr;
  }
  float d0[4], d1[4];
  mma_b0(d0, T.f8a, pack_b(a[0], a[1]), pack_b(b[0], b[1]));
  mma_b0(d1, T.f8a, pack_b(a[2], a[3]), pack_b(b[2], b[3]));
#pragma unroll
  for (int i = 0; i < 2; i++) {
    const float c0 = __uint_as_float(comp(T.ti0, 2 * i)), s0 = __uint_as_float(comp(T.ti0, 2 * i + 1));
    const float c1 = __uint_as_float(comp(T.ti1, 2 * i)), s1 = __uint_as_float(comp(T.ti1, 2 * i + 1));
    a[i] = d0[i] * c0 - d0[2 + i] * s0;     b[i] = d0[2 + i] * c0 + d0[i] * s0;
    a[2 + i] = d1[i] * c1 - d1[2 + i] * s1; b[2 + i] = d1[2 + i] * c1 + d1[i] * s1;
  }
  const uint32_t pr0 = pack_b(a[0], a[1]), pr1 = pack_b(a[2], a[3]), pi0 = pack_b(b[0], b[1]), pi1 = pack_b(b[2], b[3]);
  mma_b0(re, T.gc, pr0, pr1); mma_b0(im, T.gs, pr0, pr1);
  mma_b(re, T.gn, pi0, pi1); mma_b(im, T.gc, pi0, pi1);
#pragma unroll
  for (int e = 0; e < 4; e++) o[e] = pack_b(re[e], im[e]);
}
__device__ __forceinline__ void load_btab_fwd(BTab& T, uint32_t tab) {
  T.fc = lds128(tab + 14 * 512); T.fs = lds128(tab + 15 * 512); T.fn = lds128(tab + 16 * 512);
  T.tw = lds128(tab + 17 * 512); T.f8b = lds128(tab + 18 * 512);
}
__device__ __forceinline__ void load_btab_inv(BTab& T, uint32_t tab) {
  T.f8a = lds128(tab + 19 * 512); T.ti0 = lds128(tab + 20 * 512); T.ti1 = lds128(tab + 21 * 512);
  T.gc = lds128(tab + 22 * 512); T.gs = lds128(tab + 23 * 512); T.gn = lds128(tab + 24 * 512);
}

__device__ __forceinline__ float shfl_xor_v(float v, int m) { float r; asm volatile("shfl.sync.bfly.b32 %0, %1, %2, 31, -1;" : "=f"(r) : "f"(v), "r"(m)); return r; }
template <class F>
__device__ __forceinline__ void row_stats2(float sa, float qa, float sb, float qb, int lane, float& ra, float& ma, float& rb, float& mb, F filler) {
  const bool lo = lane < 16;
  const float s1 = shfl_xor_v(lo ? sb : sa, 16), q1 = shfl_xor_v(lo ? qb : qa, 16);
  filler(0);
  float s = (lo ? sa : sb) + s1, q = (lo ? qa : qb) + q1;
#pragma unroll
  for (int k = 1; k < 5; k++) {
    const float s2 = shfl_xor_v(s, 16 >> k), q2 = shfl_xor_v(q, 16 >> k);
    filler(k);
    s += s2; q += q2;
  }
  const float mean = s * (1.f / 512.f);
  const float var = fmaxf(q * (1.f / 512.f) - mean * mean, 0.f);
  const float r = rsqrtf(var + 1e-5f), m = -mean * r;
  const float r2 = shfl_xor_v(r, 16), m2 = shfl_xor_v(m, 16);
  filler(5);
  ra = lo ? r : r2; ma = lo ? m : m2; rb = lo ? r2 : r; mb = lo ? m2 : m;
}

__device__ __forceinline__ float gelu_mul(float g, float u) {
  const float z = g * fmaf(g * g, 0.10091094891335171f, 1.1283791670955126f);
  const float gu = g * u;
  return fmaf(gu, ftanh(z), gu);
}

struct Params {
  const __nv_bfloat16* x;
  const uint4* tab;
  const __nv_bfloat16 *wr, *wi, *wg, *wu, *wd;
  __nv_bfloat16* out;
};

__device__ __forceinline__ void issue_w_slot(uint32_t sb, int kc, int slot, int j, const CUtensorMap* mg, const CUtensorMap* mu) {
  const uint32_t bar = sb + BAR_FULL + slot * 8, s = sb + slot * SLOT;
  tma3d(s + 8192, mg, 176 * j, 32 * kc, 0, bar);
  tma3d(s + 16384, mu, 176 * j, 32 * kc, 0, bar);
  bulk_g2s(s + 24576, g_W + (size_t)(j * 16 + kc) * 384, 6144, bar);
}

__device__ __forceinline__ void ffn_role(int cta, int& jf, int& rbf) {
  const int cl = cta >> 1, i = cl - 4;
  const int grp = cl < 4 ? 0 : i < 32 ? (i & 7) : (i - 32) % 7 + 1;
  const int idx = cl < 4 ? 4 + cl : i < 32 ? (i >> 3) : 4 + (i - 32) / 7;
  jf = 2 * (grp & 3) + (cta & 1);
  rbf = 8 * (grp >> 2) + idx;
}

__global__ void __cluster_dims__(2, 1, 1) __launch_bounds__(NTHREADS, 1)
fused_kernel(const Params P, const __grid_constant__ CUtensorMap tmG, const __grid_constant__ CUtensorMap tmU,
             const __grid_constant__ CUtensorMap tmGt, const __grid_constant__ CUtensorMap tmUt,
             const __grid_constant__ CUtensorMap tmD, const __grid_constant__ CUtensorMap tmO,
             const __grid_constant__ CUtensorMap tmFr, const __grid_constant__ CUtensorMap tmFi) {
  extern __shared__ __align__(1024) unsigned char smem_raw[];
  const uint32_t sb = smem_u32(smem_raw);
  const int tid = threadIdx.x, warp = tid >> 5, lane = tid & 31, g = lane >> 2, q = lane & 3;
  const int cta = blockIdx.x;
  if (warp < 8) {
#pragma unroll
    for (int i = 0; i < 2; i++)
      if (i < 1 || tid < 192) asm volatile("cp.async.cg.shared.global [%0], [%1], 16;" ::"r"(sb + OFF_TAB + (i * 256 + tid) * 16), "l"(P.tab + i * 256 + tid) : "memory");
  }
  uint2 ra[4], rb[4];
  {
    const __nv_bfloat16* xa = P.x + (size_t)(128 * (warp & 7) + cta) * D_ + 32 * q + 4 * g;
#pragma unroll
    for (int j = 0; j < 4; j++) { ra[j] = ldg_nc64_if(xa + 128 * j, warp < 8); rb[j] = ldg_nc64_if(xa + (size_t)1024 * D_ + 128 * j, warp < 8); }
  }
  PROFD(0, 26, 0);
  const uint32_t tab = sb + OFF_TAB + lane * 16;
  if (warp >= 8) {
    if ((sb & 0x3FFFF) != SMEM_BASE) TRAP(5);
    int jf, rbf;
    ffn_role(cta, jf, rbf);
    asm volatile("setmaxnreg.dec.sync.aligned.u32 %0;" ::"n"(REG_SIDE));
    if (lane == 0) {
      if (warp == 9 || warp == 10) {
#pragma unroll
        for (int i = 0; i < 7; i++) {
          if (warp == 9 && i < NSLOT) mbar_init(sb + BAR_EMPTY + 8 * i, 8);
          else mbar_init(sb + BAR_RECV + 8 * (warp == 9 ? 0 : i + 1), 1);
        }
        if (warp == 10) mbar_init(sb + BAR_FILT, 1);
      } else if (warp == 8) {
        mbar_init(sb + BAR_TABB, 1);
        mbar_expect(sb + BAR_TABB, TAB_BYTES - TAB_A_BYTES);
        bulk_g2s(sb + OFF_TAB + TAB_A_BYTES, (const char*)P.tab + TAB_A_BYTES, TAB_BYTES - TAB_A_BYTES, sb + BAR_TABB);
        mbar_init(sb + BAR_PEER, 1);
      } else if (warp == 11) {
        mbar_init(sb + BAR_PACK, 1);
#pragma unroll
        for (int i = 0; i < NSLOT; i++) { mbar_init(sb + BAR_FULL + 8 * i, 1); mbar_expect(sb + BAR_FULL + 8 * i, SLOT); }
      }
      asm volatile("fence.mbarrier_init.release.cluster;" ::: "memory");
    }
    __syncwarp();
    unsigned* const c1 = g_ctl, * const c2 = g_ctl + 32, * const c3 = g_ctl + 64, * const c4 = g_ctl + 96, * const cW = g_ctl + 112;
    if (warp == 11) {
      const unsigned c1v = ldg_relaxed32(c1);
      if (lane == 0) {
        mbar_expect(sb + BAR_PACK, 6144);
        tma3d(sb + 24576, &tmGt, 0, 32 * (cta & 15), 11 * (cta >> 4) + 8, sb + BAR_PACK);
        tma3d(sb + 27648, &tmUt, 0, 32 * (cta & 15), 11 * (cta >> 4) + 8, sb + BAR_PACK);
        asm volatile("prefetch.tensormap [%0];" ::"l"(&tmG) : "memory");
        asm volatile("prefetch.tensormap [%0];" ::"l"(&tmU) : "memory");
        asm volatile("prefetch.tensormap [%0];" ::"l"(&tmD) : "memory");
        asm volatile("prefetch.tensormap [%0];" ::"l"(&tmO) : "memory");
        sts32(sb + OFF_MISC + 8, (c1v >> 7) + 1);
      }
      __syncwarp();
      bar_sync(9, 352);
      bar_arrive(3, 352);
      if (lane == 0) {
        l2_prefetch((const char*)P.wg + cta * 11008, 11008);
        l2_prefetch((const char*)P.wu + cta * 11008, 11008);
        l2_prefetch((const char*)P.wd + cta * 11008, 11008);
        mbar_wait(sb + BAR_PACK, 0);
        PROF(1, 11);
      }
      __syncwarp();
      bar_sync(10, 288);
      if (lane == 0) {
        bulk_s2g(g_W + (size_t)cta * 384, sb + 24576, 6144);
        bulk_commit();
        bulk_wait_all();
        fence_release_gpu();
        red_add(cW + (cta >> 4));
        PROF(1, 7);
      }
      __syncwarp();
      bar_sync(8, 288);
      if (lane == 0) {
        poll_ge<true>(cW + jf, lds32(sb + OFF_MISC + 8) << 4);
        fence_async_global();
        PROF(1, 8);
#pragma unroll
        for (int kc = 0; kc < NSLOT - 1; kc++) issue_w_slot(sb, kc, kc, jf, &tmG, &tmU);
        PROF(1, 9);
        const unsigned ep = lds32(sb + OFF_MISC + 8);
        poll_ge<true>(c3 + rbf, ep << 3);
        fence_async_global();
        PROF(1, 5);
#pragma unroll
        for (int kc = 0; kc < NSLOT - 1; kc++) bulk_g2s(sb + kc * SLOT, g_A + (size_t)(rbf * 16 + kc) * 512, 8192, sb + BAR_FULL + 8 * kc);
      }
      __syncwarp();
      bar_sync(6, 320);
      if (lane == 0) {
        const unsigned ep = lds32(sb + OFF_MISC + 8);
        int slot = NSLOT - 1, ph = 1;
#pragma unroll 1
        for (int it = NSLOT - 1; it < 24; it++) {
          if (it == 10) { poll_ge<true>(c4 + rbf, ep << 3); mbar_wait_cluster(sb + BAR_PEER, 0); fence_async_global(); }
          mbar_wait(sb + BAR_EMPTY + 8 * slot, ph);
          const uint32_t s = sb + slot * SLOT, bar = sb + BAR_FULL + 8 * slot;
          if (it < 16) {
            if (it >= NSLOT) mbar_expect(bar, SLOT);
            issue_w_slot(sb, it, slot, jf, &tmG, &tmU);
            bulk_g2s(s, g_A + (size_t)(rbf * 16 + it) * 512, 8192, bar);
          } else {
            const int pi = it - 16;
            mbar_expect(bar, 22528);
            tma2d(s + 8192, &tmD, 256 * (jf & 1) + 64 * ((pi & 1) + 2 * (pi >> 2)), 176 * (jf ^ ((pi >> 1) & 1)), bar);
          }
          if (++slot == NSLOT) { slot = 0; ph ^= 1; }
        }
        PROF(1, 6);
      }
      return;
    }
    if (warp == 10) {
      if (lane == 0) {
        const int c0 = ((cta >> 3) * DF_ + 32 * (cta & 7)) & ~7;
        mbar_expect(sb + BAR_FILT, 20480);
        tma2d(sb + OFF_FILT, &tmFr, c0, 0, sb + BAR_FILT);
        tma2d(sb + OFF_FILT + 10240, &tmFi, c0, 0, sb + BAR_FILT);
      }
      __syncwarp();
      bar_arrive(9, 352);
      bar_arrive(7, 352);
      return;
    }
    if (warp == 9) {
      unsigned cv = 0;
      if (lane < 7) cv = ldg_relaxed32(g_ctl + (lane < 2 ? 32 * lane : lane < 4 ? 48 + 8 * lane : 64 + 8 * lane));
      bar_arrive(9, 352);
      bar_arrive(7, 352);
      const unsigned ep = (__shfl_sync(~0u, cv, 0) >> 7) + 1;
      {
        const unsigned span = lane == 1 ? 128u : lane == 6 ? 16u : 8u;
        if (lane >= 1 && lane < 7 && cv - span * (ep - 1) > span) TRAP(7);
      }
      bar_sync(2, 288);
      if (lane == 0) { spin(DELAY1, sb + OFF_MISC); red_add(c1); PROF(1, 0); poll_ge<false>(c1, ep << 7); PROF(1, 1); }
      __syncwarp();
      bar_arrive(3, 352);
      bar_sync(2, 288);
      if (lane == 0) { spin(DELAY2, sb + OFF_MISC); red_add(c2); PROF(1, 2); poll_ge<false>(c2, ep << 7); PROF(1, 3); }
      __syncwarp();
      bar_arrive(3, 320);
      bar_sync(2, 288);
      if (lane == 0) { fence_release_gpu(); red_add(c3 + (cta >> 3)); PROF(1, 4); }
      __syncwarp();
      bar_sync(6, 320);
      if (lane < 16) { bulk_s2g(P.out + (size_t)(128 * lane + cta) * D_, sb + OFF_FILT + lane * 1024, 1024); bulk_commit(); bulk_wait_all(); }
      __syncwarp();
      if (lane == 0) {
        asm volatile("mbarrier.arrive.release.cluster.shared::cluster.b64 _, [%0];" ::"r"(mapa(sb + BAR_PEER, (cta & 1) ^ 1)) : "memory");
        fence_release_gpu(); red_add(c4 + (cta >> 3));
      }
      return;
    }
    const int k1B = cta >> 3, blkB = cta & 7;
    const unsigned c1v = ldg_relaxed32(c1);
    float cf[8];
#pragma unroll
    for (int w = 0; w < 8; w++) cf[w] = 0.25f * fcos(ang2048((lane >> 1) * (128 * w + cta) + 512 * (lane & 1)));
    const uint32_t par = ((c1v >> 7) + 1) & 1u;
    if (lane == 0) sts32(sb + OFF_MISC, par);
    bar_sync(4, 288);
    {
      float v = 0.f;
#pragma unroll
      for (int w = 0; w < 8; w++) {
        const uint32_t z = lds32(sb + OFF_X + (8 + w) * XPLANE + 8 * XBLK);
        const float2 f = __half22float2(*reinterpret_cast<const __half2*>(&z));
        v = fmaf(cf[w], (lane & 2) ? f.x - f.y : f.x + f.y, v);
      }
      const float o = __shfl_down_sync(~0u, v, 1);
      if (!(lane & 1)) stg_relaxed32(g_G1x + cta * 16 + (lane >> 1), tag(pack_h(v, o), par));
    }
    bar_sync(7, 352);
    bar_sync(3, 352);
    if (blkB == 7) {
      uint32_t r[4];
#pragma unroll
      for (int j = 0; j < 4; j++) r[j] = ldg_relaxed32(g_G1x + (16 * q + g + 8 * (j & 1) + 64 * (j >> 1)) * 16 + k1B);
      mbar_wait(sb + BAR_TABB, 0);
      BTab T;
      load_btab_fwd(T, tab);
      load_btab_inv(T, tab);
      mbar_wait(sb + BAR_FILT, 0);
      float nr[4], ni[4];
#pragma unroll
      for (int e = 0; e < 4; e++) {
        const uint32_t ad = sb + OFF_FILT + (g + 8 * (e >> 1) + 16 * (2 * q + (e & 1))) * 80 + ((k1B * DF_) & 7) * 2 + 64;
        uint32_t a, b;
        asm volatile("ld.shared.u16 %0, [%1];" : "=r"(a) : "r"(ad) : "memory");
        asm volatile("ld.shared.u16 %0, [%1];" : "=r"(b) : "r"(ad + 10240) : "memory");
        nr[e] = blo(a); ni[e] = blo(b);
      }
#pragma unroll
      for (int j = 0; j < 4; j++)
        if ((r[j] ^ par) & 1u) r[j] = reload32(g_G1x + (16 * q + g + 8 * (j & 1) + 64 * (j >> 1)) * 16 + k1B, par);
      uint32_t o[4];
      phaseB_col(T, r[0], r[1], r[2], r[3], nr, ni, o);
#pragma unroll
      for (int e = 0; e < 4; e++) stg_relaxed32(g_G2x + k1B * 128 + 8 * (g + 8 * (e >> 1)) + 2 * q + (e & 1), tag(o[e], par));
    }
    float cc[8], cs[8];
#pragma unroll
    for (int i = 0; i < 8; i++) {
      const float th = ang2048((8 * (lane & 1) + i) * (128 * (lane >> 1) + cta));
      cc[i] = 0.25f * fcos(th); cs[i] = -0.25f * fsin(th);
    }
    bar_sync(3, 320);
    {
      uint32_t r[8];
#pragma unroll
      for (int i = 0; i < 8; i++) r[i] = ldg_relaxed32(g_G2x + (8 * (lane & 1) + i) * 128 + cta);
      float v = 0.f;
#pragma unroll
      for (int i = 0; i < 8; i++) {
        if ((r[i] ^ par) & 1u) r[i] = reload32(g_G2x + (8 * (lane & 1) + i) * 128 + cta, par);
        v = fmaf(cc[i], blo(r[i]), fmaf(cs[i], bhi(r[i]), v));
      }
      v += __shfl_xor_sync(~0u, v, 1);
      const float o = __shfl_down_sync(~0u, v, 16);
      if (lane < 16 && !(lane & 1)) sts32(sb + OFF_X + (8 + (lane >> 1)) * XPLANE + 8 * XBLK, pack_b(v, o));
    }
    bar_arrive(4, 288);
    asm volatile("exit;");
  }
  {
    PROFD(0, 28, 0);
    if (tid == 0) mbar_init(sb + BAR_TABA, 256);
    bar_sync(5, 256);
    asm volatile("cp.async.mbarrier.arrive.noinc.shared::cta.b64 [%0];" ::"r"(sb + BAR_TABA) : "memory");
    uint32_t m3[2][4][2];
    {
      const uint32_t sgn = (g & 2) ? 0x80008000u : 0u;
      const int off = ((g & 2) ? -256 : 256) + 512 * (g & 1);
#pragma unroll
      for (int u = 0; u < 4; u++)
#pragma unroll
        for (int h = 0; h < 2; h++) {
          const float th = ang2048((4 * u + (g >> 1)) * (128 * (q + 4 * h) + cta) + off);
          const uint32_t w = pack_h(fcos(th) * 0.17677669529663687f, fsin(th) * 0.17677669529663687f);
          m3[0][u][h] = w;
          m3[1][u][h] = __byte_perm(w, w, 0x1032) ^ sgn;
        }
    }
    PROFD(0, 18, m3[1][3][1] ^ m3[0][0][0] ^ m3[0][2][1]);
    asm volatile("setmaxnreg.inc.sync.aligned.u32 %0;" ::"n"(REG_CONS));
    PROFD(0, 19, 0);
    PROFD(0, 20, ra[0].x);
    PROFD(0, 0, rb[3].y);
    {
      float va[4][4], vb[4][4];
      float sa = 0.f, qa = 0.f, sb_ = 0.f, qb = 0.f;
#pragma unroll
      for (int j = 0; j < 4; j++) {
        va[j][0] = blo(ra[j].x); va[j][1] = bhi(ra[j].x); va[j][2] = blo(ra[j].y); va[j][3] = bhi(ra[j].y);
        vb[j][0] = blo(rb[j].x); vb[j][1] = bhi(rb[j].x); vb[j][2] = blo(rb[j].y); vb[j][3] = bhi(rb[j].y);
#pragma unroll
        for (int t = 0; t < 4; t++) { sa += va[j][t]; qa = fmaf(va[j][t], va[j][t], qa); sb_ += vb[j][t]; qb = fmaf(vb[j][t], vb[j][t], qb); }
      }
      asm volatile("" : "+f"(sa), "+f"(qa), "+f"(sb_), "+f"(qb)::"memory");
      bar_arrive(9, 352);
      mbar_wait(sb + BAR_TABA, 0);
      uint4 ta[14];
      float r_a, m_a, r_b, m_b;
      row_stats2(sa, qa, sb_, qb, lane, r_a, m_a, r_b, m_b, [&](int k) {
#pragma unroll
        for (int i = 0; i < 14; i++) if (i / 2 == k || (k == 5 && i >= 12)) ta[i] = lds128(tab + i * 512);
      });
      PROFD(0, 1, __float_as_uint(r_a));
      const uint4 fc = ta[0], fs = ta[1], fn = make_uint4(fs.x ^ 0x80008000u, fs.y ^ 0x80008000u, fs.z ^ 0x80008000u, fs.w ^ 0x80008000u);
      float dre[4][4], dim[4][4];
#pragma unroll
      for (int t = 0; t < 4; t++) {
        const uint32_t a0 = pack_h(fmaf(va[0][t], r_a, m_a), fmaf(va[1][t], r_a, m_a)), a1 = pack_h(fmaf(va[2][t], r_a, m_a), fmaf(va[3][t], r_a, m_a));
        const uint32_t b0 = pack_h(fmaf(vb[0][t], r_b, m_b), fmaf(vb[1][t], r_b, m_b)), b1 = pack_h(fmaf(vb[2][t], r_b, m_b), fmaf(vb[3][t], r_b, m_b));
        mma_h0(dre[t], fc, a0, a1); mma_h0(dim[t], fc, b0, b1);
        mma_h(dre[t], fs, b0, b1); mma_h(dim[t], fn, a0, a1);
      }
      uint32_t ar[2][4], ai[2][4];
#pragma unroll
      for (int t = 0; t < 4; t++)
#pragma unroll
        for (int hf = 0; hf < 2; hf++) {
          twiddle_h2(pack_h(dre[t][2 * hf], dre[t][2 * hf + 1]), pack_h(dim[t][2 * hf], dim[t][2 * hf + 1]),
                     comp(ta[2 + t], 2 * hf), comp(ta[2 + t], 2 * hf + 1), ar[t >> 1][2 * (t & 1) + hf], ai[t >> 1][2 * (t & 1) + hf]);
        }
      PROFD(0, 24, ai[1][3]);
      if (HINT1 == -2) { asm volatile("" : "+r"(ar[0][0]), "+r"(ai[1][3])::"memory"); bar_arrive(2, 288); asm volatile("" : "+r"(ar[0][0]), "+r"(ar[1][0]), "+r"(ai[0][0]), "+r"(ai[1][0])::"memory"); }
      const uint32_t xp = sb + OFF_X + warp * XPLANE + q * XBLK + g * 4;
      const uint32_t xm = sb + OFF_X + (8 + warp) * XPLANE + (15 - q) * XBLK + (16 - g) * 4;
#pragma unroll
      for (int up = 0; up < 2; up++) {
        float zr[2][4], zi[2][4];
#pragma unroll
        for (int ks = 0; ks < 2; ks++) {
          const uint4 cv = ta[6 + 2 * ks + up], sv = ta[10 + 2 * ks + up];
          const uint32_t n0 = ar[ks][0] ^ 0x80008000u, n1 = ar[ks][1] ^ 0x80008000u, n2 = ar[ks][2] ^ 0x80008000u, n3 = ar[ks][3] ^ 0x80008000u;
          if (ks == 0) {
            mma_h0(zr[0], ar[ks][0], ar[ks][1], ar[ks][2], ar[ks][3], cv.x, cv.y);
            mma_h0(zr[1], ar[ks][0], ar[ks][1], ar[ks][2], ar[ks][3], cv.z, cv.w);
            mma_h0(zi[0], ai[ks][0], ai[ks][1], ai[ks][2], ai[ks][3], cv.x, cv.y);
            mma_h0(zi[1], ai[ks][0], ai[ks][1], ai[ks][2], ai[ks][3], cv.z, cv.w);
          } else {
            mma_h(zr[0], ar[ks][0], ar[ks][1], ar[ks][2], ar[ks][3], cv.x, cv.y);
            mma_h(zr[1], ar[ks][0], ar[ks][1], ar[ks][2], ar[ks][3], cv.z, cv.w);
            mma_h(zi[0], ai[ks][0], ai[ks][1], ai[ks][2], ai[ks][3], cv.x, cv.y);
            mma_h(zi[1], ai[ks][0], ai[ks][1], ai[ks][2], ai[ks][3], cv.z, cv.w);
          }
          mma_h(zr[0], ai[ks][0], ai[ks][1], ai[ks][2], ai[ks][3], sv.x, sv.y);
          mma_h(zr[1], ai[ks][0], ai[ks][1], ai[ks][2], ai[ks][3], sv.z, sv.w);
          mma_h(zi[0], n0, n1, n2, n3, sv.x, sv.y);
          mma_h(zi[1], n0, n1, n2, n3, sv.z, sv.w);
        }
#pragma unroll
        for (int uu = 0; uu < 2; uu++)
#pragma unroll
          for (int e = 0; e < 4; e++) {
            const int u = 2 * up + uu, hf = e >> 1, i = e & 1;
            const uint32_t w = pack_h(zr[uu][e], zi[uu][e]);
            if (up == 0) {
              sts32(xp + u * 4 * XBLK + (8 * hf + 16 * i) * 4, w);
              if (u == 0 && e == 0 && lane == 0) sts32(sb + OFF_X + (8 + warp) * XPLANE, w);
            } else {
              sts32(xm - u * 4 * XBLK + (16 * (1 - i) - 8 * hf) * 4 + ((e == 0 && g == 0) ? 32 : 0), w);
            }
          }
      }
      PROF(0, 2);
      bar_sync(4, 288);
      if (HINT1 == -1) bar_arrive(2, 288);
      const uint32_t par = lds32(sb + OFF_MISC);
      PROFD(0, 25, par);
      float acc[4][2][4];
#pragma unroll
      for (int sg = 0; sg < 2; sg++) {
        const uint4 v0 = lds128(sb + OFF_X + (8 * sg + q) * XPLANE + warp * XBLK + g * 16);
        const uint4 v1 = lds128(sb + OFF_X + (8 * sg + 4 + q) * XPLANE + warp * XBLK + g * 16);
#pragma unroll
        for (int u = 0; u < 4; u++) {
          if (sg == 0) {
            mma_h0(acc[u][0], v0.x, v0.y, v1.x, v1.y, m3[sg][u][0], m3[sg][u][1]);
            mma_h0(acc[u][1], v0.z, v0.w, v1.z, v1.w, m3[sg][u][0], m3[sg][u][1]);
          } else {
            mma_h(acc[u][0], v0.x, v0.y, v1.x, v1.y, m3[sg][u][0], m3[sg][u][1]);
            mma_h(acc[u][1], v0.z, v0.w, v1.z, v1.w, m3[sg][u][0], m3[sg][u][1]);
          }
        }
      }
#pragma unroll
      for (int u = 0; u < 4; u++) {
        const uint4 o = make_uint4(tag(pack_h(acc[u][0][0], acc[u][0][1]), par), pack_h(acc[u][0][2], acc[u][0][3]),
                                   tag(pack_h(acc[u][1][0], acc[u][1][1]), par), pack_h(acc[u][1][2], acc[u][1][3]));
        if (u == HINT1) bar_arrive(2, 288);
        stg_relaxed128(g_G1 + ((((4 * u + q) * 8 + warp) * 128 + cta) * 8 + g), o);
      }
      if (HINT1 == 4) bar_arrive(2, 288);
      PROF(0, 3);
#pragma unroll
      for (int j = 0; j < 4; j++) {
        asm volatile("st.shared.v2.u32 [%0], {%1,%2};" ::"r"(sb + warp * 1024 + j * 256 + q * 64 + g * 8), "r"(ra[j].x), "r"(ra[j].y) : "memory");
        asm volatile("st.shared.v2.u32 [%0], {%1,%2};" ::"r"(sb + SLOT + warp * 1024 + j * 256 + q * 64 + g * 8), "r"(rb[j].x), "r"(rb[j].y) : "memory");
      }
      __syncwarp();
    }
    const uint32_t par = lds32(sb + OFF_MISC);
    {
      mbar_wait(sb + BAR_TABB, 0);
      BTab T;
      load_btab_fwd(T, tab);
      load_btab_inv(T, tab);
      bar_sync(7, 352);
      mbar_wait(sb + BAR_FILT, 0);
      uint2 fwr[4], fwi[4];
      auto load_filter = [&](int e) {
        const int o = ((((cta >> 3) * DF_) & 7) * 2) + 8 * warp, sh = (o & 2) * 8;
        const uint32_t ad = sb + OFF_FILT + (g + 8 * (e >> 1) + 16 * (2 * q + (e & 1))) * 80 + (o & ~3);
        const uint32_t a0 = lds32(ad), a1 = lds32(ad + 4), a2 = lds32(ad + 8);
        const uint32_t b0 = lds32(ad + 10240), b1 = lds32(ad + 10244), b2 = lds32(ad + 10248);
        fwr[e] = make_uint2(__funnelshift_r(a0, a1, sh), __funnelshift_r(a1, a2, sh));
        fwi[e] = make_uint2(__funnelshift_r(b0, b1, sh), __funnelshift_r(b1, b2, sh));
      };
      const int row0 = tid >> 3, ch = tid & 7;
      const uint4* src = g_G1 + (cta * 128 + row0) * 8 + ch;
      const uint32_t stw = sb + OFF_X + row0 * 128 + ((ch ^ ((row0 ^ (row0 >> 3)) & 7)) << 4);
      bar_sync(3, 352);
      PROF(0, 4);
      uint4 v[4];
      load4_validated<0>(v, src, par, [&]() { load_filter(0); load_filter(1); load_filter(2); load_filter(3); });
#pragma unroll
      for (int j = 0; j < 4; j++) sts128((stw ^ ((j & 1) << 6)) + j * 4096, v[j]);
      PROFD(0, 5, v[3].x);
      bar_arrive(10, 288);
      bar_sync(1, 256);
      if (HINT2 == -3) bar_arrive(2, 288);
#pragma unroll
      for (int j = 0; j < 4; j++) {
        const int row = 16 * q + g + 8 * (j & 1) + 64 * (j >> 1);
        v[j] = lds128(sb + OFF_X + row * 128 + ((warp ^ ((row ^ (row >> 3)) & 7)) << 4));
      }
      if (HINT2 == -2) { bar_arrive(2, 288); asm volatile("" : "+r"(v[0].x), "+r"(v[1].y), "+r"(v[2].z), "+r"(v[3].w), "+r"(v[0].y), "+r"(v[0].z), "+r"(v[0].w)::"memory"); }
      uint32_t o[4][4];
#pragma unroll
      for (int c = 0; c < 4; c++) {
        float wr[4], wi[4];
#pragma unroll
        for (int e = 0; e < 4; e++) {
          const uint32_t a = (c & 2) ? fwr[e].y : fwr[e].x, b = (c & 2) ? fwi[e].y : fwi[e].x;
          wr[e] = (c & 1) ? bhi(a) : blo(a); wi[e] = (c & 1) ? bhi(b) : blo(b);
        }
        phaseB_col(T, comp(v[0], c), comp(v[1], c), comp(v[2], c), comp(v[3], c), wr, wi, o[c]);
      }
      if (HINT2 == -1) { asm volatile("" : "+r"(o[0][0]), "+r"(o[1][1]), "+r"(o[2][2]), "+r"(o[3][3])::"memory"); bar_arrive(2, 288); }
#pragma unroll
      for (int e = 0; e < 4; e++) {
        const int row = 8 * (g + 8 * (e >> 1)) + 2 * q + (e & 1);
        sts128(sb + OFF_X + row * 128 + ((warp ^ ((row ^ (row >> 3)) & 7)) << 4), make_uint4(tag(o[0][e], par), o[1][e], tag(o[2][e], par), o[3][e]));
      }
      PROF(0, 6);
      bar_sync(1, 256);
#pragma unroll
      for (int j = 0; j < 4; j++) {
        const int row = row0 + 32 * j;
        v[j] = lds128((stw ^ ((j & 1) << 6)) + j * 4096);
        if (j == HINT2) bar_arrive(2, 288);
        stg_relaxed128(g_G2 + (row * 128 + cta) * 8 + ch, v[j]);
      }
      if (HINT2 == 4) bar_arrive(2, 288);
      PROF(0, 7);
    }
    {
      uint4 xr[2][2], tc[19], v[4];
      uint32_t mi[2][4][2];
      const uint4* src = g_G2 + ((cta * 16 + q) * 8 + warp) * 8 + g;
      {
        int cta = blockIdx.x;
        asm volatile("" : "+r"(cta)::"memory");
        const uint32_t sgn = ((q ^ g) & 1) ? 0x80000000u : 0x00008000u;
        const int off = ((q & 1) ? -256 : 256) - 512 * (g & 1);
#pragma unroll
        for (int j2 = 0; j2 < 2; j2++)
#pragma unroll
          for (int h = 0; h < 2; h++)
#pragma unroll
            for (int uu = 0; uu < 2; uu++) {
              const float th = ang2048((8 * j2 + 4 * h + q) * (128 * (4 * uu + (g >> 1)) + cta) + off);
              const uint32_t w = pack_b(fcos(th) * 0.35355339059327373f, fsin(th) * -0.35355339059327373f);
              mi[j2][uu][h] = w;
              mi[j2][2 + uu][h] = __byte_perm(w, w, 0x1032) ^ sgn;
            }
      }
#pragma unroll
      for (int h2 = 0; h2 < 2; h2++) { xr[0][h2] = lds128(sb + warp * 1024 + h2 * 512 + lane * 16); xr[1][h2] = lds128(sb + SLOT + warp * 1024 + h2 * 512 + lane * 16); }
#pragma unroll
      for (int i = 0; i < 19; i++) tc[i] = lds128(tab + (22 + i) * 512);
      bar_sync(3, 320);
      PROF(0, 8);
      load4_validated<1>(v, src, par, []() {});
      PROFD(0, 9, v[3].x);
      bar_arrive(8, 288);
#pragma unroll
      for (int u = 0; u < 4; u++) {
        float a0[4], a1[4];
        mma_b0(a0, v[0].x, v[0].y, v[1].x, v[1].y, mi[0][u][0], mi[0][u][1]);
        mma_b0(a1, v[0].z, v[0].w, v[1].z, v[1].w, mi[0][u][0], mi[0][u][1]);
        mma_b(a0, v[2].x, v[2].y, v[3].x, v[3].y, mi[1][u][0], mi[1][u][1]);
        mma_b(a1, v[2].z, v[2].w, v[3].z, v[3].w, mi[1][u][0], mi[1][u][1]);
        sts128(sb + OFF_X + (4 * u + q) * XPLANE + warp * XBLK + g * 16,
               make_uint4(pack_b(a0[0], a0[1]), pack_b(a0[2], a0[3]), pack_b(a1[0], a1[1]), pack_b(a1[2], a1[3])));
      }
      bar_sync(4, 288);
      PROF(0, 10);
      const uint32_t xp = sb + OFF_X + warp * XPLANE + q * XBLK + g * 4;
      const uint32_t xm = sb + OFF_X + (8 + warp) * XPLANE + (15 - q) * XBLK + (16 - g) * 4;
      uint32_t br[2][4], bi[2][4];
#pragma unroll
      for (int t = 0; t < 2; t++)
#pragma unroll
        for (int u = 0; u < 4; u++) {
          uint32_t w0, w1;
          if (u < 2) {
            w0 = lds32(xp + u * 4 * XBLK + 8 * t * 4);
            w1 = lds32(xp + u * 4 * XBLK + (8 * t + 16) * 4);
            if (u == 0 && t == 0) {
              const uint32_t wm = lds32(sb + OFF_X + (8 + warp) * XPLANE);
              const uint32_t av = pack_b(0.5f * (blo(w0) + blo(wm)), 0.5f * (bhi(w0) + bhi(wm)));
              w0 = lane == 0 ? av : w0;
            }
          } else {
            w0 = lds32(xm - u * 4 * XBLK + (16 - 8 * t) * 4 + ((t == 0 && g == 0) ? 32 : 0));
            w1 = lds32(xm - u * 4 * XBLK - 8 * t * 4);
          }
          br[t][u] = plo(w0, w1);
          bi[t][u] = phi(w0, w1);
        }
      uint32_t pr[2][2][2], pi[2][2][2];
#pragma unroll
      for (int mt = 0; mt < 2; mt++) {
        float re[2][4], im[2][4];
#pragma unroll
        for (int ks = 0; ks < 2; ks++) {
          const uint4 cv = tc[3 + 2 * mt + ks], sv = tc[7 + 2 * mt + ks];
#pragma unroll
          for (int t = 0; t < 2; t++) {
            if (ks == 0) { mma_b0(re[t], cv, br[t][0], br[t][1]); mma_b0(im[t], cv, bi[t][0], bi[t][1]); }
            else { mma_b(re[t], cv, br[t][2], br[t][3]); mma_b(im[t], cv, bi[t][2], bi[t][3]); }
          }
#pragma unroll
          for (int t = 0; t < 2; t++) {
            mma_b(re[t], sv, bi[t][2 * ks] ^ 0x80008000u, bi[t][2 * ks + 1] ^ 0x80008000u);
            mma_b(im[t], sv, br[t][2 * ks], br[t][2 * ks + 1]);
          }
        }
#pragma unroll
        for (int t = 0; t < 2; t++)
#pragma unroll
          for (int hf = 0; hf < 2; hf++) {
            const uint4 tw = tc[11 + 4 * mt + 2 * t + hf];
            const float c0 = __uint_as_float(tw.x), s0 = __uint_as_float(tw.y), c1 = __uint_as_float(tw.z), s1 = __uint_as_float(tw.w);
            const float r0 = re[t][2 * hf], i0 = im[t][2 * hf], r1 = re[t][2 * hf + 1], i1 = im[t][2 * hf + 1];
            pr[mt][hf][t] = pack_b(r0 * c0 - i0 * s0, r1 * c1 - i1 * s1);
            pi[mt][hf][t] = pack_b(i0 * c0 + r0 * s0, i1 * c1 + r1 * s1);
          }
      }
      const uint4 gcv = tc[0], gsv = tc[1], gnv = tc[2];
      float ha[2][8], hb[2][8];
#pragma unroll
      for (int mt = 0; mt < 2; mt++)
#pragma unroll
        for (int hf = 0; hf < 2; hf++) {
          float re[4], im[4];
#pragma unroll
          for (int e = 0; e < 4; e++) {
            const int el = 4 * (e & 1) + 2 * mt + hf;
            const uint32_t wa = comp(xr[0][e >> 1], el >> 1), wb = comp(xr[1][e >> 1], el >> 1);
            re[e] = (el & 1) ? bhi(wa) : blo(wa);
            im[e] = (el & 1) ? bhi(wb) : blo(wb);
          }
          mma_b(re, gcv, pr[mt][hf][0], pr[mt][hf][1]); mma_b(im, gsv, pr[mt][hf][0], pr[mt][hf][1]);
          mma_b(re, gnv, pi[mt][hf][0], pi[mt][hf][1]); mma_b(im, gcv, pi[mt][hf][0], pi[mt][hf][1]);
#pragma unroll
          for (int e = 0; e < 4; e++) { ha[e >> 1][4 * (e & 1) + 2 * mt + hf] = re[e]; hb[e >> 1][4 * (e & 1) + 2 * mt + hf] = im[e]; }
        }
      float sa = 0.f, qa = 0.f, sb_ = 0.f, qb = 0.f;
#pragma unroll
      for (int h2 = 0; h2 < 2; h2++)
#pragma unroll
        for (int e = 0; e < 8; e++) { sa += ha[h2][e]; qa = fmaf(ha[h2][e], ha[h2][e], qa); sb_ += hb[h2][e]; qb = fmaf(hb[h2][e], hb[h2][e], qb); }
      float r_a, m_a, r_b, m_b;
      row_stats2(sa, qa, sb_, qb, lane, r_a, m_a, r_b, m_b, [](int) {});
      r_a *= 0.70710678118654752f; m_a *= 0.70710678118654752f; r_b *= 0.70710678118654752f; m_b *= 0.70710678118654752f;
      const int r8 = cta & 7, ma = 64 * (r8 >> 2) + 4 * warp + (r8 & 3), mb = ma + 32;
      uint4* dstA = g_A + (size_t)((cta >> 3) * 16 + g) * 512;
      auto store_ln = [&](int h2) {
        uint4 oa, ob;
        oa.x = pack_b(fmaf(ha[h2][0], r_a, m_a), fmaf(ha[h2][1], r_a, m_a)); oa.y = pack_b(fmaf(ha[h2][2], r_a, m_a), fmaf(ha[h2][3], r_a, m_a));
        oa.z = pack_b(fmaf(ha[h2][4], r_a, m_a), fmaf(ha[h2][5], r_a, m_a)); oa.w = pack_b(fmaf(ha[h2][6], r_a, m_a), fmaf(ha[h2][7], r_a, m_a));
        ob.x = pack_b(fmaf(hb[h2][0], r_b, m_b), fmaf(hb[h2][1], r_b, m_b)); ob.y = pack_b(fmaf(hb[h2][2], r_b, m_b), fmaf(hb[h2][3], r_b, m_b));
        ob.z = pack_b(fmaf(hb[h2][4], r_b, m_b), fmaf(hb[h2][5], r_b, m_b)); ob.w = pack_b(fmaf(hb[h2][6], r_b, m_b), fmaf(hb[h2][7], r_b, m_b));
        stg_relaxed128(dstA + h2 * 8 * 512 + ma * 4 + (q ^ ((ma >> 1) & 3)), oa);
        stg_relaxed128(dstA + h2 * 8 * 512 + mb * 4 + (q ^ ((mb >> 1) & 3)), ob);
      };
      store_ln(0);
      store_ln(1);
      bar_arrive(2, 288);
      PROF(0, 11);
#pragma unroll
      for (int h2 = 0; h2 < 2; h2++) {
        sts128(sb + OFF_FILT + warp * 1024 + h2 * 512 + lane * 16,
               make_uint4(pack_b(ha[h2][0], ha[h2][1]), pack_b(ha[h2][2], ha[h2][3]), pack_b(ha[h2][4], ha[h2][5]), pack_b(ha[h2][6], ha[h2][7])));
        sts128(sb + OFF_FILT + (warp + 8) * 1024 + h2 * 512 + lane * 16,
               make_uint4(pack_b(hb[h2][0], hb[h2][1]), pack_b(hb[h2][2], hb[h2][3]), pack_b(hb[h2][4], hb[h2][5]), pack_b(hb[h2][6], hb[h2][7])));
      }
      fence_async_smem();
      bar_arrive(6, 320);
    }
    {
      const int wg = warp >> 2;
      if (lane == 0) mbar_expect(sb + BAR_RECV + 8 * warp, 5632);
      int jf, rbf;
      ffn_role(cta, jf, rbf);
      float accA[128], accB[48];
      const uint64_t dA = mkdesc(0, 16, 512, 2) + (uint64_t)(__shfl_sync(~0u, wg, 0) * 256);
      constexpr uint64_t dM = mkdesc(8192, 4096, 1024, 1), dT = mkdesc(24576, 1024, 256, 3);
      int slot = 0, ph = 0;
#pragma unroll 1
      for (int kc = 0; kc < 16; kc++) {
        const bool yield = kc == PP0 && wg == 1;
        if (yield) {
          wg_wait<0>();
          if (lane == 0) mbar_arrive(sb + BAR_EMPTY + 8 * ((PP0 - 1) % NSLOT));
          bar_sync(14, 256);
        }
        mbar_wait(sb + BAR_FULL + 8 * slot, ph);
        if (kc == 0) PROF(0, 12);
        const uint64_t so = (uint64_t)(slot * (SLOT >> 4));
        wg_fence();
        wgmma_ss_n256(accA, dA + so, dM + so, kc > 0);
        wgmma_ss_n96(accB, dA + so, dT + so, kc > 0);
        wgmma_ss_n256(accA, dA + so + 2, dM + so + 128, 1);
        wgmma_ss_n96(accB, dA + so + 2, dT + so + 32, 1);
        wg_commit();
        if (kc > 0) {
          wg_wait<1>();
          if (lane == 0 && !yield) mbar_arrive(sb + BAR_EMPTY + 8 * (slot == 0 ? NSLOT - 1 : slot - 1));
        }
        if (++slot == NSLOT) { slot = 0; ph ^= 1; }
      }
      bar_arrive(13 + (wg ^ 1), 256);
      wg_wait<0>();
      reg_fence(accA); reg_fence(accB);
      if (lane == 0) mbar_arrive(sb + BAR_EMPTY + 8 * 3);
      PROF(0, 13);
      uint32_t hh[11][4], hp[11][4];
      const uint32_t rank = cta & 1;
      const uint32_t rdst = mapa(sb + OFF_RECV + warp * 5632 + lane * 16, rank ^ 1), rbar = mapa(sb + BAR_RECV + 8 * warp, rank ^ 1);
#pragma unroll
      for (int ks = 0; ks < 11; ks++) {
#pragma unroll
        for (int r = 0; r < 4; r++) {
          const int i = (ks < 8 ? 8 * ks : 8 * (ks - 8)) + 2 * r;
          if (ks < 8) hh[ks][r] = pack_b(gelu_mul(accA[i], accA[64 + i]), gelu_mul(accA[i + 1], accA[65 + i]));
          else hh[ks][r] = pack_b(gelu_mul(accB[i], accB[24 + i]), gelu_mul(accB[i + 1], accB[25 + i]));
        }
        asm volatile("st.async.weak.shared::cluster.mbarrier::complete_tx::bytes.v4.b32 [%0], {%1,%2,%3,%4}, [%5];"
                     ::"r"(rdst + ks * 512), "r"(hh[ks][0]), "r"(hh[ks][1]), "r"(hh[ks][2]), "r"(hh[ks][3]), "r"(rbar) : "memory");
      }
      PROFD(0, 14, hh[10][3]);
      float acc2[64];
      constexpr uint64_t dD = mkdesc(8192, SLOT, 1024, 1);
      const uint32_t st01 = (sb + OFF_RECV + warp * 5632 + 1023) & ~1023u;
      const int srow = (lane & 7) + 8 * ((lane >> 3) & 1);
      auto epilogue = [&](int pr) {
        const uint32_t stg = st01;
        if (pr == 1) { if (lane < 2) bulk_wait_read(); __syncwarp(); }
#pragma unroll
        for (int j = 0; j < 16; j += 2) {
          const uint32_t ad = stg + (j >> 3) * 2048 + srow * 128 + ((((j & 7) + (lane >> 4)) ^ (lane & 7)) << 4);
          asm volatile("stmatrix.sync.aligned.m8n8.x4.shared.b16 [%0], {%1,%2,%3,%4};" ::"r"(ad),
                       "r"(pack_b(acc2[4 * j], acc2[4 * j + 1])), "r"(pack_b(acc2[4 * j + 2], acc2[4 * j + 3])),
                       "r"(pack_b(acc2[4 * j + 4], acc2[4 * j + 5])), "r"(pack_b(acc2[4 * j + 6], acc2[4 * j + 7])) : "memory");
        }
        fence_async_smem();
        __syncwarp();
        if (lane < 2) { tma3d_red_add(&tmO, 256 * rank + 128 * pr + 64 * lane, 8 * rbf + 4 * wg, 4 * (warp & 3), stg + lane * 2048); bulk_commit(); }
      };
      bar_sync(13 + wg, 256);
      mbar_wait(sb + BAR_FULL + 8 * 4, 0);
      mbar_wait(sb + BAR_FULL + 8 * 5, 0);
      wg_fence();
#pragma unroll
      for (int ks = 0; ks < 11; ks++) wgmma_rs_n128<0>(acc2, hh[ks][0], hh[ks][1], hh[ks][2], hh[ks][3], dD + (uint64_t)(4 * (SLOT >> 4) + ks * 128), ks > 0);
      wg_commit();
      mbar_wait_cluster(sb + BAR_RECV + 8 * warp, 0);
#pragma unroll
      for (int ks = 0; ks < 11; ks++) {
        const uint4 v = lds128(sb + OFF_RECV + warp * 5632 + ks * 512 + lane * 16);
        hp[ks][0] = v.x; hp[ks][1] = v.y; hp[ks][2] = v.z; hp[ks][3] = v.w;
      }
      mbar_wait(sb + BAR_FULL + 8 * 0, 1);
      mbar_wait(sb + BAR_FULL + 8 * 1, 1);
      wg_fence();
#pragma unroll
      for (int ks = 0; ks < 11; ks++) {
        wgmma_rs_n128<0>(acc2, hp[ks][0], hp[ks][1], hp[ks][2], hp[ks][3], dD + (uint64_t)(ks * 128), 1);
        if (ks == 1) {
          wg_commit();
          wg_wait<1>();
          if (lane < 2) mbar_arrive(sb + BAR_EMPTY + 8 * (4 + lane));
          wg_fence();
        }
      }
      wg_commit();
      bar_arrive(13 + (wg ^ 1), 256);
      wg_wait<0>();
      reg_fence(acc2);
      PROF(0, 15);
      epilogue(0);
      bar_sync(13 + wg, 256);
      mbar_wait(sb + BAR_FULL + 8 * 2, 1);
      mbar_wait(sb + BAR_FULL + 8 * 3, 1);
      wg_fence();
#pragma unroll
      for (int ks = 0; ks < 11; ks++) wgmma_rs_n128<0>(acc2, hh[ks][0], hh[ks][1], hh[ks][2], hh[ks][3], dD + (uint64_t)(2 * (SLOT >> 4) + ks * 128), ks > 0);
      wg_commit();
      mbar_wait(sb + BAR_FULL + 8 * 4, 1);
      mbar_wait(sb + BAR_FULL + 8 * 5, 1);
      wg_fence();
#pragma unroll
      for (int ks = 0; ks < 11; ks++) wgmma_rs_n128<0>(acc2, hp[ks][0], hp[ks][1], hp[ks][2], hp[ks][3], dD + (uint64_t)(4 * (SLOT >> 4) + ks * 128), 1);
      wg_commit();
      if (wg == 0) bar_arrive(14, 256);
      wg_wait<0>();
      reg_fence(acc2);
      PROF(0, 16);
      epilogue(1);
      if (lane < 2) bulk_wait_read();
      PROF(0, 17);
    }
    }
}

typedef CUresult (*EncodeFn)(CUtensorMap*, CUtensorMapDataType, cuuint32_t, void*, const cuuint64_t*, const cuuint64_t*,
                             const cuuint32_t*, const cuuint32_t*, CUtensorMapInterleave, CUtensorMapSwizzle,
                             CUtensorMapL2promotion, CUtensorMapFloatOOBfill);

bool make_map(EncodeFn fn, CUtensorMap* m, const void* base, int rank, const cuuint64_t* dims, const cuuint64_t* strides,
              const cuuint32_t* box, CUtensorMapSwizzle sw) {
  const cuuint32_t es[3] = {1, 1, 1};
  return fn(m, CU_TENSOR_MAP_DATA_TYPE_BFLOAT16, rank, const_cast<void*>(base), dims, strides, box, es,
            CU_TENSOR_MAP_INTERLEAVE_NONE, sw, CU_TENSOR_MAP_L2_PROMOTION_L2_128B, CU_TENSOR_MAP_FLOAT_OOB_FILL_NONE) == CUDA_SUCCESS;
}

}

extern "C" void kernel_launch(void* const* d_in, const int* in_sizes, int n_in, void* d_out, int out_size) {
  (void)in_sizes; (void)n_in; (void)out_size;
  Params P;
  P.x = (const __nv_bfloat16*)d_in[0];
  P.wr = (const __nv_bfloat16*)d_in[1];
  P.wi = (const __nv_bfloat16*)d_in[2];
  P.wg = (const __nv_bfloat16*)d_in[4];
  P.wu = (const __nv_bfloat16*)d_in[5];
  P.wd = (const __nv_bfloat16*)d_in[6];
  P.out = (__nv_bfloat16*)d_out;
  static EncodeFn encode = nullptr;
  static void* tab_addr = nullptr;
  if (!encode) {
    void* fn = nullptr;
    cudaDriverEntryPointQueryResult qr;
    if (cudaGetDriverEntryPoint("cuTensorMapEncodeTiled", &fn, cudaEnableDefault, &qr) != cudaSuccess || !fn) return;
    if (cudaGetSymbolAddress(&tab_addr, g_tab) != cudaSuccess) return;
    encode = (EncodeFn)fn;
    cudaFuncSetAttribute(fused_kernel, cudaFuncAttributeMaxDynamicSharedMemorySize, SMEM_BYTES);
  }
  P.tab = (const uint4*)tab_addr;
  CUtensorMap tG, tU, tGt, tUt, tD, tO, tFr, tFi;
  bool ok = true;
  {
    const cuuint64_t dims[3] = {F_, D_, 2}, str[2] = {F_ * 2, 128};
    const cuuint32_t box[3] = {64, 32, 2};
    ok &= make_map(encode, &tG, P.wg, 3, dims, str, box, CU_TENSOR_MAP_SWIZZLE_128B);
    ok &= make_map(encode, &tU, P.wu, 3, dims, str, box, CU_TENSOR_MAP_SWIZZLE_128B);
  }
  {
    const cuuint64_t dims[3] = {16, D_, F_ / 16}, str[2] = {F_ * 2, 32};
    const cuuint32_t box[3] = {16, 32, 3};
    ok &= make_map(encode, &tGt, P.wg, 3, dims, str, box, CU_TENSOR_MAP_SWIZZLE_32B);
    ok &= make_map(encode, &tUt, P.wu, 3, dims, str, box, CU_TENSOR_MAP_SWIZZLE_32B);
  }
  {
    const cuuint64_t dims[2] = {D_, F_}, str[1] = {D_ * 2};
    const cuuint32_t box[2] = {64, 176};
    ok &= make_map(encode, &tD, P.wd, 2, dims, str, box, CU_TENSOR_MAP_SWIZZLE_128B);
  }
  {
    const cuuint64_t dims[3] = {D_, 128, 16}, str[2] = {D_ * 2, 128 * D_ * 2};
    const cuuint32_t box[3] = {64, 4, 4};
    ok &= make_map(encode, &tO, P.out, 3, dims, str, box, CU_TENSOR_MAP_SWIZZLE_128B);
  }
  {
    const cuuint64_t dims[2] = {16 * DF_, 128}, str[1] = {16 * DF_ * 2};
    const cuuint32_t box[2] = {40, 128};
    ok &= make_map(encode, &tFr, P.wr, 2, dims, str, box, CU_TENSOR_MAP_SWIZZLE_NONE);
    ok &= make_map(encode, &tFi, P.wi, 2, dims, str, box, CU_TENSOR_MAP_SWIZZLE_NONE);
  }
  if (!ok) return;
  fused_kernel<<<NCTA, NTHREADS, SMEM_BYTES, cudaStreamPerThread>>>(P, tG, tU, tGt, tUt, tD, tO, tFr, tFi);
}
```
